```python
import torch

def _softmax(x, axis=-1):
    return torch.softmax(x, dim=axis)
def _gelu(x):
    return torch.nn.functional.gelu(x, approximate="tanh")
def _silu(x):
    return torch.nn.functional.silu(x)
def _sigmoid(x):
    return torch.sigmoid(x)
def _layernorm(x, axis=-1, eps=1e-5):
    m = x.mean(dim=axis, keepdim=True)
    v = x.var(dim=axis, keepdim=True, unbiased=False)
    return (x - m) / torch.sqrt(v + eps)
def _scatter_add(tgt, idx, src, axis=0):
    return tgt.clone().index_add_(axis, idx, src)
def _segment_sum(src, seg, n):
    out = torch.zeros((n,) + src.shape[1:], dtype=src.dtype)
    return out.index_add_(0, seg, src)
def _pad(x, pw):
    flat = tuple(v for pair in reversed(pw) for v in pair)
    return torch.nn.functional.pad(x, flat)

kernel_name = 'standalone__edge_featured_mpnn_egc__graph'

def setup_inputs():

    _w = (lambda a: (lambda t: t.to(torch.bfloat16) if t.is_floating_point() else t)(torch.as_tensor(a)))
    N, deg, D, De = 10000, 16, 128, max(16, 1)
    E = N * deg
    return {
        "x": _w((lambda *s: torch.randn(*s, dtype=torch.bfloat16) * 0.1)(N, D)),
        "e_attr": _w((lambda *s: torch.randn(*s, dtype=torch.bfloat16) * 0.1)(E, De)),
        "src": _w((lambda lo, hi, *s: torch.randint(lo, hi, s))(0, N, E).to(torch.int64)),
        "dst": _w((lambda lo, hi, *s: torch.randint(lo, hi, s))(0, N, E).to(torch.int64)),
        "u_w": _w((lambda *s: torch.randn(*s, dtype=torch.bfloat16) * 0.05)(D, D)),
        "v_w": _w((lambda *s: torch.randn(*s, dtype=torch.bfloat16) * 0.05)(D, D)),
        "g_w": _w((lambda *s: torch.randn(*s, dtype=torch.bfloat16) * 0.1)(2 * D + De, D)),
    }

def reference(x, e_attr, src, dst, u_w, v_w, g_w):
    N, D = x.shape
    g_in = torch.concatenate([x[dst], x[src], e_attr], axis=-1)
    eta = _sigmoid(g_in @ g_w)
    hv = x @ v_w
    msg = eta * hv[src]
    agg = _segment_sum(msg, dst, N)
    return _silu(x @ u_w + agg)
```

```cpp
#include <cuda_runtime.h>
#include <cuda_bf16.h>
#include <cuda.h>
#include <stdint.h>

namespace egc {

typedef __nv_bfloat16 bf16;

constexpr int NN = 10000, EE = 160000;
constexpr int NCTA = 132, NPC = 76, ECH = 1216, NTHR = 512;
constexpr int PIECES = 10, XCAP = 3 * PIECES;
constexpr int TCAP = 96;
constexpr int NSEG = (EE + TCAP - 1) / TCAP;

constexpr int STAGE = 4352;
constexpr int SM_R0 = 0;
constexpr int SM_R1 = 16 * STAGE;
constexpr int SM_S = SM_R1 + 8 * STAGE;
constexpr int SM_WA = SM_R1 + 16 * STAGE;
constexpr int SM_X = SM_WA + 32768;
constexpr int SM_C = SM_X + 20480;
constexpr int SM_LSE = SM_C + 4096;
constexpr int SM_LID = SM_LSE + 6144 + 128;
constexpr int SM_HIST = SM_LID + 1536 + 32;
constexpr int SM_KEYS = SM_HIST + 544;
constexpr int SM_CURS = SM_KEYS + 512;
constexpr int SM_DBIN = SM_CURS + 512;
constexpr int SM_TDEG = SM_DBIN + 256;
constexpr int SM_TNODE = SM_TDEG + 512;
constexpr int SM_TCNT = SM_TNODE + 128;
constexpr int SM_FLAG = SM_TCNT + 64;
constexpr int SM_BAR = SM_FLAG + 16;
constexpr int SM_TRACE = SM_BAR + 9 * 8 + 8;
constexpr int SM_END = SM_TRACE + 2 * 48 * 4;
constexpr int SMEM_BYTES = SM_END + 1024;

__device__ __align__(1024) uint4 g_table[NN * 32];
__device__ __align__(1024) uint4 g_xch[NCTA * NCTA * PIECES];
__device__ __align__(128) unsigned g_bar[32];
#define TRACE(i) do {} while (0)

__device__ __forceinline__ void mma16816(float* d, uint32_t a0, uint32_t a1, uint32_t a2, uint32_t a3, uint32_t b0, uint32_t b1) {
    asm("mma.sync.aligned.m16n8k16.row.col.f32.bf16.bf16.f32 {%0,%1,%2,%3}, {%4,%5,%6,%7}, {%8,%9}, {%0,%1,%2,%3};"
        : "+f"(d[0]), "+f"(d[1]), "+f"(d[2]), "+f"(d[3]) : "r"(a0), "r"(a1), "r"(a2), "r"(a3), "r"(b0), "r"(b1));
}
__device__ __forceinline__ void mma16816_z(float* d, uint32_t a0, uint32_t a1, uint32_t a2, uint32_t a3, uint32_t b0, uint32_t b1) {
    asm("mma.sync.aligned.m16n8k16.row.col.f32.bf16.bf16.f32 {%0,%1,%2,%3}, {%4,%5,%6,%7}, {%8,%9}, {%10,%10,%10,%10};"
        : "=f"(d[0]), "=f"(d[1]), "=f"(d[2]), "=f"(d[3]) : "r"(a0), "r"(a1), "r"(a2), "r"(a3), "r"(b0), "r"(b1), "f"(0.f));
}
__device__ __forceinline__ void mma1688(float* d, uint32_t a0, uint32_t a1, uint32_t b0) {
    asm("mma.sync.aligned.m16n8k8.row.col.f32.bf16.bf16.f32 {%0,%1,%2,%3}, {%4,%5}, {%6}, {%0,%1,%2,%3};"
        : "+f"(d[0]), "+f"(d[1]), "+f"(d[2]), "+f"(d[3]) : "r"(a0), "r"(a1), "r"(b0));
}
__device__ __forceinline__ void mma1688_z(float* d, uint32_t a0, uint32_t a1, uint32_t b0) {
    asm("mma.sync.aligned.m16n8k8.row.col.f32.bf16.bf16.f32 {%0,%1,%2,%3}, {%4,%5}, {%6}, {%7,%7,%7,%7};"
        : "=f"(d[0]), "=f"(d[1]), "=f"(d[2]), "=f"(d[3]) : "r"(a0), "r"(a1), "r"(b0), "f"(0.f));
}
__device__ __forceinline__ void ldsm4(uint32_t* r, uint32_t addr) {
    asm volatile("ldmatrix.sync.aligned.m8n8.x4.shared.b16 {%0,%1,%2,%3}, [%4];" : "=r"(r[0]), "=r"(r[1]), "=r"(r[2]), "=r"(r[3]) : "r"(addr) : "memory");
}
__device__ __forceinline__ void ldsm4t(uint32_t* r, uint32_t addr) {
    asm volatile("ldmatrix.sync.aligned.m8n8.x4.trans.shared.b16 {%0,%1,%2,%3}, [%4];" : "=r"(r[0]), "=r"(r[1]), "=r"(r[2]), "=r"(r[3]) : "r"(addr) : "memory");
}
__device__ __forceinline__ void ldsm2(uint32_t* r, uint32_t addr) {
    asm volatile("ldmatrix.sync.aligned.m8n8.x2.shared.b16 {%0,%1}, [%2];" : "=r"(r[0]), "=r"(r[1]) : "r"(addr) : "memory");
}
__device__ __forceinline__ void stsm4t(uint32_t addr, uint32_t r0, uint32_t r1, uint32_t r2, uint32_t r3) {
    asm volatile("stmatrix.sync.aligned.m8n8.x4.trans.shared.b16 [%0], {%1,%2,%3,%4};" :: "r"(addr), "r"(r0), "r"(r1), "r"(r2), "r"(r3) : "memory");
}
__device__ __forceinline__ float tanh_ap(float x) { float r; asm("tanh.approx.f32 %0, %1;" : "=f"(r) : "f"(x)); return r; }
__device__ __forceinline__ uint32_t pack_bf16(float lo, float hi) { uint32_t r; asm("cvt.rn.bf16x2.f32 %0, %1, %2;" : "=r"(r) : "f"(hi), "f"(lo)); return r; }
__device__ __forceinline__ uint32_t fma_bf16x2(uint32_t a, uint32_t b, uint32_t c) { uint32_t r; asm("fma.rn.bf16x2 %0, %1, %2, %3;" : "=r"(r) : "r"(a), "r"(b), "r"(c)); return r; }
__device__ __forceinline__ uint32_t mul_bf16x2(uint32_t a, uint32_t b) { uint32_t r; asm("mul.rn.bf16x2 %0, %1, %2;" : "=r"(r) : "r"(a), "r"(b)); return r; }
__device__ __forceinline__ uint32_t seteq_bf16x2(uint32_t a, uint32_t b) { uint32_t r; asm("set.eq.bf16x2.bf16x2 %0, %1, %2;" : "=r"(r) : "r"(a), "r"(b)); return r; }
__device__ __forceinline__ uint32_t prmt(uint32_t a, uint32_t b, uint32_t s) { uint32_t r; asm("prmt.b32 %0, %1, %2, %3;" : "=r"(r) : "r"(a), "r"(b), "r"(s)); return r; }
__device__ __forceinline__ uint32_t shl_clamp(uint32_t a, uint32_t s) { uint32_t r; asm("shl.b32 %0, %1, %2;" : "=r"(r) : "r"(a), "r"(s)); return r; }
__device__ __forceinline__ void cp16(uint32_t dst, const void* src) { asm volatile("cp.async.cg.shared.global [%0], [%1], 16;" :: "r"(dst), "l"(src) : "memory"); }
__device__ __forceinline__ void cp16z(uint32_t dst, const void* src, uint32_t sz) { asm volatile("cp.async.cg.shared.global [%0], [%1], 16, %2;" :: "r"(dst), "l"(src), "r"(sz) : "memory"); }
__device__ __forceinline__ void cp_commit() { asm volatile("cp.async.commit_group;" ::: "memory"); }
template <int N> __device__ __forceinline__ void cp_wait() { asm volatile("cp.async.wait_group %0;" :: "n"(N) : "memory"); }
__device__ __forceinline__ uint4 lds128(uint32_t a) { uint4 v; asm volatile("ld.shared.v4.u32 {%0,%1,%2,%3}, [%4];" : "=r"(v.x), "=r"(v.y), "=r"(v.z), "=r"(v.w) : "r"(a) : "memory"); return v; }
__device__ __forceinline__ uint2 lds64(uint32_t a) { uint2 v; asm volatile("ld.shared.v2.u32 {%0,%1}, [%2];" : "=r"(v.x), "=r"(v.y) : "r"(a) : "memory"); return v; }
__device__ __forceinline__ uint32_t lds32(uint32_t a) { uint32_t v; asm volatile("ld.shared.u32 %0, [%1];" : "=r"(v) : "r"(a) : "memory"); return v; }
__device__ __forceinline__ uint32_t lds8(uint32_t a) { uint32_t v; asm volatile("ld.shared.u8 %0, [%1];" : "=r"(v) : "r"(a) : "memory"); return v; }
__device__ __forceinline__ void sts32(uint32_t a, uint32_t v) { asm volatile("st.shared.u32 [%0], %1;" :: "r"(a), "r"(v) : "memory"); }
__device__ __forceinline__ void sts8(uint32_t a, uint32_t v) { asm volatile("st.shared.u8 [%0], %1;" :: "r"(a), "r"(v) : "memory"); }
__device__ __forceinline__ void sts128(uint32_t a, uint4 v) { asm volatile("st.shared.v4.u32 [%0], {%1,%2,%3,%4};" :: "r"(a), "r"(v.x), "r"(v.y), "r"(v.z), "r"(v.w) : "memory"); }
__device__ __forceinline__ uint32_t atoms_add(uint32_t a, uint32_t v) { uint32_t r; asm volatile("atom.shared.add.u32 %0, [%1], %2;" : "=r"(r) : "r"(a), "r"(v) : "memory"); return r; }
__device__ __forceinline__ void reds_add(uint32_t a, uint32_t v) { asm volatile("red.shared.add.u32 [%0], %1;" :: "r"(a), "r"(v) : "memory"); }
__device__ __forceinline__ uint32_t atoms_add_p(bool p, uint32_t a, uint32_t v) {
    uint32_t r = 0;
    asm volatile("{\n.reg .pred p;\nsetp.ne.u32 p, %3, 0;\n@p atom.shared.add.u32 %0, [%1], %2;\n}" : "+r"(r) : "r"(a), "r"(v), "r"((uint32_t)p) : "memory");
    return r;
}
__device__ __forceinline__ uint32_t lds32_p(bool p, uint32_t a) {
    uint32_t r = 0;
    asm volatile("{\n.reg .pred p;\nsetp.ne.u32 p, %2, 0;\n@p ld.shared.u32 %0, [%1];\n}" : "+r"(r) : "r"(a), "r"((uint32_t)p) : "memory");
    return r;
}
__device__ __forceinline__ void sts32_p(bool p, uint32_t a, uint32_t v) {
    asm volatile("{\n.reg .pred p;\nsetp.ne.u32 p, %2, 0;\n@p st.shared.u32 [%0], %1;\n}" :: "r"(a), "r"(v), "r"((uint32_t)p) : "memory");
}
__device__ __forceinline__ void sts8_p(bool p, uint32_t a, uint32_t v) {
    asm volatile("{\n.reg .pred p;\nsetp.ne.u32 p, %2, 0;\n@p st.shared.u8 [%0], %1;\n}" :: "r"(a), "r"(v), "r"((uint32_t)p) : "memory");
}
__device__ __forceinline__ void st_piece(uint4* p, uint4 v) {
    asm volatile("{\n.reg .b128 q;\n.reg .b64 lo, hi;\nmov.b64 lo, {%1,%2};\nmov.b64 hi, {%3,%4};\nmov.b128 q, {lo, hi};\nst.relaxed.gpu.global.b128 [%0], q;\n}"
                 :: "l"(p), "r"(v.x), "r"(v.y), "r"(v.z), "r"(v.w) : "memory");
}
__device__ __forceinline__ uint4 ld_piece(const uint4* p) {
    uint4 v;
    asm volatile("{\n.reg .b128 q;\n.reg .b64 lo, hi;\nld.relaxed.gpu.global.b128 q, [%4];\nmov.b128 {lo, hi}, q;\nmov.b64 {%0,%1}, lo;\nmov.b64 {%2,%3}, hi;\n}"
                 : "=r"(v.x), "=r"(v.y), "=r"(v.z), "=r"(v.w) : "l"(p) : "memory");
    return v;
}
__device__ __forceinline__ void mbar_init(uint32_t bar, uint32_t cnt) { asm volatile("mbarrier.init.shared::cta.b64 [%0], %1;" :: "r"(bar), "r"(cnt) : "memory"); }
__device__ __forceinline__ void mbar_expect(uint32_t bar, uint32_t bytes) { asm volatile("mbarrier.arrive.expect_tx.shared::cta.b64 _, [%0], %1;" :: "r"(bar), "r"(bytes) : "memory"); }
__device__ __forceinline__ void mbar_wait(uint32_t bar, uint32_t parity) {
    uint32_t ok; int it = 0;
    do {
        asm volatile("{\n.reg .pred p;\nmbarrier.try_wait.parity.shared::cta.b64 p, [%1], %2;\nselp.u32 %0, 1, 0, p;\n}" : "=r"(ok) : "r"(bar), "r"(parity) : "memory");
    } while (!ok && ++it < (1 << 22));
}
__device__ __forceinline__ void tma_load2d(uint32_t dst, const CUtensorMap* tm, int c0, int c1, uint32_t bar) {
    asm volatile("cp.async.bulk.tensor.2d.shared::cluster.global.mbarrier::complete_tx::bytes [%0], [%1, {%3, %4}], [%2];"
                 :: "r"(dst), "l"(tm), "r"(bar), "r"(c0), "r"(c1) : "memory");
}
__device__ __forceinline__ void tma_load2d_mc(uint32_t dst, const CUtensorMap* tm, int c0, int c1, uint32_t bar) {
    asm volatile("cp.async.bulk.tensor.2d.shared::cluster.global.mbarrier::complete_tx::bytes.multicast::cluster [%0], [%1, {%3, %4}], [%2], %5;"
                 :: "r"(dst), "l"(tm), "r"(bar), "r"(c0), "r"(c1), "h"((uint16_t)3) : "memory");
}
__device__ __forceinline__ void tma_store2d(const CUtensorMap* tm, int c0, int c1, uint32_t src) {
    asm volatile("cp.async.bulk.tensor.2d.global.shared::cta.bulk_group [%0, {%2, %3}], [%1];"
                 :: "l"(tm), "r"(src), "r"(c0), "r"(c1) : "memory");
}
__device__ __forceinline__ void lt_bar() { asm volatile("bar.sync 3, 256;" ::: "memory"); }
__device__ __forceinline__ void wg_bar(int id) { asm volatile("bar.sync %0, 128;" :: "r"(id) : "memory"); }

__device__ __forceinline__ void wgmma_n80(float (&d)[40], uint64_t da, uint64_t db, int acc) {
    asm volatile("{\n.reg .pred p;\nsetp.ne.b32 p, %42, 0;\n"
        "wgmma.mma_async.sync.aligned.m64n80k16.f32.bf16.bf16 "
        "{%0,%1,%2,%3,%4,%5,%6,%7,%8,%9,%10,%11,%12,%13,%14,%15,%16,%17,%18,%19,"
        "%20,%21,%22,%23,%24,%25,%26,%27,%28,%29,%30,%31,%32,%33,%34,%35,%36,%37,%38,%39}, "
        "%40, %41, p, 1, 1, 1, 0;\n}\n"
        : "+f"(d[0]), "+f"(d[1]), "+f"(d[2]), "+f"(d[3]), "+f"(d[4]), "+f"(d[5]), "+f"(d[6]), "+f"(d[7]), "+f"(d[8]), "+f"(d[9]),
          "+f"(d[10]), "+f"(d[11]), "+f"(d[12]), "+f"(d[13]), "+f"(d[14]), "+f"(d[15]), "+f"(d[16]), "+f"(d[17]), "+f"(d[18]), "+f"(d[19]),
          "+f"(d[20]), "+f"(d[21]), "+f"(d[22]), "+f"(d[23]), "+f"(d[24]), "+f"(d[25]), "+f"(d[26]), "+f"(d[27]), "+f"(d[28]), "+f"(d[29]),
          "+f"(d[30]), "+f"(d[31]), "+f"(d[32]), "+f"(d[33]), "+f"(d[34]), "+f"(d[35]), "+f"(d[36]), "+f"(d[37]), "+f"(d[38]), "+f"(d[39])
        : "l"(da), "l"(db), "r"(acc));
}

__device__ __forceinline__ void gemm_issue(float (&d)[40], uint32_t wbase, uint32_t xbase) {
    asm volatile("wgmma.fence.sync.aligned;" ::: "memory");
#pragma unroll
    for (int s = 0; s < 8; s++) {
        const uint32_t aa = wbase + s * 2048, ab = xbase + (s >> 2) * 10240 + (s & 3) * 32;
        const uint64_t da = (uint64_t)((aa & 0x3FFFF) >> 4) | ((uint64_t)64 << 16) | ((uint64_t)64 << 32) | ((uint64_t)1 << 62);
        const uint64_t db = (uint64_t)((ab & 0x3FFFF) >> 4) | ((uint64_t)1 << 16) | ((uint64_t)64 << 32) | ((uint64_t)1 << 62);
        wgmma_n80(d, da, db, s > 0);
    }
    asm volatile("wgmma.commit_group.sync.aligned;" ::: "memory");
}
__device__ __forceinline__ void gemm_wait(float (&d)[40]) {
    asm volatile("wgmma.wait_group.sync.aligned 0;" ::: "memory");
#pragma unroll
    for (int i = 0; i < 40; i++) asm volatile("" : "+f"(d[i]) :: "memory");
}
__device__ __forceinline__ void gemm_store(const float (&d)[40], float sc, uint32_t base, int w4, int lane) {
    const int mi = lane >> 3, rr = lane & 7;
    const uint32_t sa = base + (rr + 8 * (mi >> 1)) * 128 + (((2 * w4 + (mi & 1)) ^ rr) << 4);
#pragma unroll
    for (int p = 0; p < 5; p++) {
        const float* q = d + 8 * p;
        stsm4t(sa + p * 2048, pack_bf16(q[0] * sc, q[1] * sc), pack_bf16(q[2] * sc, q[3] * sc),
               pack_bf16(q[4] * sc, q[5] * sc), pack_bf16(q[6] * sc, q[7] * sc));
    }
}

struct Params {
    const int* dst;
    const int* src;
    unsigned* bar;
    uint4* xch;
    const bf16* gw;
    const bf16* e_attr;
    const char* table;
    bf16* out;
};

__global__ void __launch_bounds__(NTHR, 1)
egc_kernel(const Params p, const __grid_constant__ CUtensorMap tm_x, const __grid_constant__ CUtensorMap tm_g,
           const __grid_constant__ CUtensorMap tm_u, const __grid_constant__ CUtensorMap tm_v, const __grid_constant__ CUtensorMap tm_t) {
    extern __shared__ unsigned char smem_raw[];
    const uint32_t sb = ((uint32_t)__cvta_generic_to_shared(smem_raw) + 1023u) & ~1023u;
    const int tid = threadIdx.x, w = tid >> 5, lane = tid & 31, b = blockIdx.x;
    const int wq = w >> 2, w4 = w & 3;
    const int g = lane >> 2, t = lane & 3, mi = lane >> 3, rr = lane & 7;
    TRACE(0);

    uint32_t Cf[8][4];
    auto load_cf = [&]() {
        const int krow = rr + 8 * (mi >> 1);
#pragma unroll
        for (int j = 0; j < 8; j++) {
            const int c = 2 * j + (mi & 1);
            ldsm4t(Cf[j], sb + SM_C + krow * 256 + ((c & 8) << 4) + (((c & 7) ^ rr) << 4));
#pragma unroll
            for (int q = 0; q < 4; q++) Cf[j][q] = mul_bf16x2(Cf[j][q], 0x3F003F00u);
        }
    };
    constexpr int LT = 256;
    if (wq < 2) {
        uint32_t epoch = 0;
        {
            const int r = tid >> 4, c = tid & 15;
            cp16(sb + SM_C + r * 256 + ((c & 8) << 4) + (((c & 7) ^ (r & 7)) << 4), p.gw + (256 + r) * 128 + c * 8);
            cp_commit();
        }
        if (tid == 0) {
            asm volatile("ld.relaxed.gpu.global.u32 %0, [%1];" : "=r"(epoch) : "l"(p.bar) : "memory");
            for (int i = 0; i < 9; i++) mbar_init(sb + SM_BAR + i * 8, 1);
            asm volatile("fence.mbarrier_init.release.cluster;" ::: "memory");
            const uint32_t bx = sb + SM_BAR;
            mbar_expect(bx, 20480);
#pragma unroll
            for (int i = 0; i < 8; i++) mbar_expect(bx + 8 + i * 8, 16384);
#define START_DELAY 1000
            if (START_DELAY > 0) { uint32_t c0, c1; asm volatile("mov.u32 %0, %%clock;" : "=r"(c0)); do { asm volatile("mov.u32 %0, %%clock;" : "=r"(c1)); } while (c1 - c0 < START_DELAY); }
            tma_load2d(sb + SM_X, &tm_x, 0, b * NPC, bx);
            tma_load2d(sb + SM_X + 10240, &tm_x, 64, b * NPC, bx);
            tma_load2d(sb + SM_R0, &tm_g, 0, 128, bx + 8);
            tma_load2d(sb + SM_R0 + 16384, &tm_g, 64, 128, bx + 16);
            tma_load2d(sb + SM_R0 + 2 * 16384, &tm_v, 0, 0, bx + 24);
            tma_load2d(sb + SM_R0 + 3 * 16384, &tm_v, 64, 0, bx + 32);
        }
        cp_wait<0>();
        asm volatile("bar.sync 6, 256;" ::: "memory");
        asm volatile("bar.arrive 8, 512;" ::: "memory");
        TRACE(1);
        load_cf();
        float d[40];
        const uint32_t wt = sb + SM_R0 + wq * 16384, bw = sb + SM_BAR + 8 + wq * 8, xt = sb + SM_X;
        const bool elect = (w4 == 0 && lane == 0);
        mbar_wait(sb + SM_BAR, 0);
        mbar_wait(bw, 0);
        TRACE(2);
        gemm_issue(d, wt, xt);
        if (tid == 0) {
#pragma unroll
            for (int i = 0; i < 2; i++) {
                tma_load2d(sb + SM_WA + i * 16384, &tm_g, i * 64, 0, sb + SM_BAR + 8 + (4 + i) * 8);
                tma_load2d(sb + SM_R1 + i * 16384, &tm_u, i * 64, 0, sb + SM_BAR + 8 + (6 + i) * 8);
            }
        }
        __syncwarp();
#pragma unroll
        for (int r = 0; r < 2; r++) {
            mbar_wait(bw + 16 * (r + 1), 0);
            gemm_wait(d);
            TRACE(3 + 2 * r);
            wg_bar(1 + wq);
            gemm_store(d, (r == 0) ? 0.5f : 0.25f, wt + r * 32768, w4, lane);
            asm volatile("fence.proxy.async.shared::cta;" ::: "memory");
            wg_bar(1 + wq);
            if (elect) {
                tma_store2d(&tm_t, (2 * r + wq) * 64, b * NPC, wt + r * 32768);
                asm volatile("cp.async.bulk.commit_group;" ::: "memory");
            }
            __syncwarp();
            gemm_issue(d, (r == 0) ? wt + 32768 : sb + SM_WA + wq * 16384, xt);
            TRACE(4 + 2 * r);
        }
        mbar_wait(bw + 48, 0);
        gemm_wait(d);
        TRACE(7);
        wg_bar(1 + wq);
        gemm_store(d, 0.5f, sb + SM_WA + wq * 16384, w4, lane);
        asm volatile("bar.sync 4, 512;" ::: "memory");
        if (elect) {
            asm volatile("cp.async.bulk.wait_group 0;" ::: "memory");
            asm volatile("fence.proxy.async.global;" ::: "memory");
            asm volatile("red.relaxed.gpu.global.add.u32 [%0], 1;" :: "l"(p.bar) : "memory");
        }
        __syncwarp();
        gemm_issue(d, sb + SM_R1 + wq * 16384, xt);
        if (tid == 0) {
            const int e0 = b * ECH, ne = min(ECH, EE - e0);
            asm volatile("cp.async.bulk.prefetch.L2.global [%0], %1;" :: "l"(p.e_attr + (size_t)e0 * 16), "r"(ne * 32) : "memory");
        }
        __syncwarp();
        TRACE(8);
        gemm_wait(d);
        wg_bar(1 + wq);
        gemm_store(d, 0.5f, sb + SM_R1 + wq * 16384, w4, lane);
        if (tid == 0) {
            uint32_t v; int it = 0;
            const uint32_t target = (epoch / (2 * NCTA) + 1) * (2 * NCTA);
            do { asm volatile("ld.relaxed.gpu.global.u32 %0, [%1];" : "=r"(v) : "l"(p.bar) : "memory"); }
            while ((int)(v - target) < 0 && ++it < (1 << 20));
        }
        __syncwarp();
        TRACE(9);
    } else {
        const int lt = tid - LT;
        int ed[5], es[5];
        uint32_t epoch;
#pragma unroll
        for (int m = 0; m < 5; m++) {
            const int k = lt + m * LT, e = b * ECH + k;
            ed[m] = ((k < ECH) && (e < EE)) ? __ldg(p.dst + e) : -1;
        }
#pragma unroll
        for (int m = 0; m < 5; m++) {
            const int k = lt + m * LT, e = b * ECH + k;
            es[m] = ((k < ECH) && (e < EE)) ? __ldg(p.src + e) : 0;
        }
        asm volatile("ld.relaxed.gpu.global.u32 %0, [%1];" : "=r"(epoch) : "l"(p.bar) : "memory");
        if (lt < 136) sts32(sb + SM_HIST + lt * 4, 0);
        if (lt < 128) { sts32(sb + SM_KEYS + lt * 4, 0); sts32(sb + SM_TDEG + lt * 4, 0); }
        if (lt < 64) sts32(sb + SM_DBIN + lt * 4, 0);
        if (lt == 0) sts32(sb + SM_FLAG, 0);
        lt_bar();
        TRACE(24);
        {
            uint32_t jj[5], rk[5];
#pragma unroll
            for (int m = 0; m < 5; m++) {
                jj[m] = (ed[m] >= 0) ? (((uint32_t)ed[m] * 55189u) >> 22) : (132 + (lane & 3));
                rk[m] = atoms_add(sb + SM_HIST + jj[m] * 4, 1);
            }
#pragma unroll
            for (int m = 0; m < 5; m++) {
                const uint32_t loc = (uint32_t)ed[m] - jj[m] * NPC;
                const uint32_t q = (rk[m] * 43691u) >> 17;
                const uint32_t off = jj[m] * (PIECES * 16) + q * 16 + (rk[m] - 3 * q + 1) * 4;
                sts32(sb + SM_S + ((ed[m] >= 0 && rk[m] < XCAP) ? off : NCTA * PIECES * 16 + lane * 4),
                      (uint32_t)es[m] | (loc << 14) | ((uint32_t)(lt + m * LT) << 21));
            }
        }
        const uint32_t bar_q = epoch / (2 * NCTA);
        epoch = (bar_q + 1) & 0xFFFFFF;
        TRACE(25);
        lt_bar();
        {
            uint4 v[6]; uint32_t c[6];
#pragma unroll
            for (int m = 0; m < 6; m++) {
                const int pc = min(lt + m * LT, NCTA * PIECES - 1);
                v[m] = lds128(sb + SM_S + pc * 16);
                c[m] = lds32(sb + SM_HIST + ((pc * 6554) >> 16) * 4);
            }
#pragma unroll
            for (int m = 0; m < 6; m++) {
                const int pc = lt + m * LT;
                if (m < 5 || pc < NCTA * PIECES) {
                    const int j = (pc * 6554) >> 16, q = pc - j * PIECES;
                    v[m].x = (epoch << 8) | min(c[m], 255u);
                    st_piece(p.xch + (((j * (PIECES / 2) + (q >> 1)) * NCTA + b) * 2 + (q & 1)), v[m]);
                }
            }
        }
        TRACE(46);
        asm volatile("bar.arrive 4, 512;" ::: "memory");
        lt_bar();
        if (lt == 0) asm volatile("red.relaxed.gpu.global.add.u32 [%0], 1;" :: "l"(p.bar + 1) : "memory");
        asm volatile("bar.sync 8, 512;" ::: "memory");
        load_cf();
        if (lt == 0) {
            uint32_t v; int it = 0;
            const uint32_t target = (bar_q + 1) * NCTA;
            do { asm volatile("ld.relaxed.gpu.global.u32 %0, [%1];" : "=r"(v) : "l"(p.bar + 1) : "memory"); }
            while ((int)(v - target) < 0 && ++it < (1 << 20));
        }
        lt_bar();
        TRACE(26);
        uint4 pv[6];
        int nval[6];
        uint32_t rk[18];
        const int pi5 = 128 + ((lt >> 1) & 3), pq5 = 2 * (lt >> 3) + (lt & 1);
        const uint4* px0 = p.xch + b * (NCTA * PIECES) + lt;
        const uint4* px5 = p.xch + b * (NCTA * PIECES) + (lt >> 3) * (2 * NCTA) + 256 + (lt & 7);
#pragma unroll
        for (int m = 0; m < 5; m++) pv[m] = ld_piece(px0 + m * (2 * NCTA));
        pv[5] = (lt < 4 * PIECES) ? ld_piece(px5) : make_uint4(epoch << 8, 0, 0, 0);
        {
            bool again; int it = 0;
            do {
                again = false;
#pragma unroll
                for (int m = 0; m < 6; m++)
                    if ((pv[m].x >> 8) != epoch) { pv[m] = ld_piece((m < 5) ? px0 + m * (2 * NCTA) : px5); again = true; }
            } while (again && ++it < (1 << 20));
        }
        const uint32_t dmy = (96 + lane) * 4;
        bool any[6];
        {
            const int cnt = pv[0].x & 255, cnt5 = pv[5].x & 255;
            if (cnt > XCAP || cnt5 > XCAP) sts32(sb + SM_FLAG, 1);
#pragma unroll
            for (int m = 0; m < 6; m++) {
                nval[m] = (m < 5) ? cnt - 3 * (2 * m + (lt & 1)) : cnt5 - 3 * pq5;
                any[m] = __any_sync(0xffffffffu, nval[m] > 0);
            }
        }
        TRACE(27);
        uint32_t ao[18];
#pragma unroll
        for (int m = 0; m < 6; m++) {
#pragma unroll
            for (int s = 0; s < 3; s++) { rk[3 * m + s] = 0; ao[3 * m + s] = dmy; }
            if (any[m]) {
#pragma unroll
                for (int s = 0; s < 3; s++) {
                    const uint32_t pl = (s == 0) ? pv[m].y : ((s == 1) ? pv[m].z : pv[m].w);
                    ao[3 * m + s] = (nval[m] > s) ? ((pl >> 12) & 0x1FC) : dmy;
                    rk[3 * m + s] = atoms_add(sb + SM_KEYS + ao[3 * m + s], 1);
                }
            }
        }
        TRACE(28);
        lt_bar();
        if (lt < 96) {
            const uint32_t deg = (lt < NPC) ? lds32(sb + SM_KEYS + lt * 4) : 0;
            const uint32_t bin = 63 - min(deg, 63u);
            const uint32_t r0 = atoms_add_p(lt < NPC, sb + SM_DBIN + bin * 4, 1);
            asm volatile("bar.sync 5, 96;" ::: "memory");
            const uint2 c2 = lds64(sb + SM_DBIN + lane * 8);
            uint32_t inc = c2.x + c2.y;
#pragma unroll
            for (int o = 1; o < 32; o <<= 1) { const uint32_t u = __shfl_up_sync(0xffffffffu, inc, o); if (lane >= o) inc += u; }
            const uint32_t ex = inc - c2.x - c2.y;
            const uint32_t pe = __shfl_sync(0xffffffffu, ex, bin >> 1), p0 = __shfl_sync(0xffffffffu, c2.x, bin >> 1);
            const int rank = pe + ((bin & 1) ? p0 : 0) + r0;
            const int k = rank >> 4, pos = rank & 15;
            const int tile = (k == 4) ? 11 - pos : ((pos < 4) ? 12 + ((k & 1) ? 3 - pos : pos) : ((k < 3) ? pos - 4 : 15 - pos));
            if (lt < NPC) {
                sts32(sb + SM_TDEG + (tile * 8 + k) * 4, deg);
                sts8(sb + SM_TNODE + tile * 8 + k, lt);
            }
            asm volatile("bar.sync 5, 96;" ::: "memory");
            if (lt < NPC) {
                const uint4 a = lds128(sb + SM_TDEG + tile * 32);
                const uint32_t a4 = lds32(sb + SM_TDEG + tile * 32 + 16);
                const uint32_t tot = a.x + a.y + a.z + a.w + a4;
                const uint32_t pre = (k > 0 ? a.x : 0) + (k > 1 ? a.y : 0) + (k > 2 ? a.z : 0) + (k > 3 ? a.w : 0);
                const uint32_t pad = (0u - tot) & 7u;
                if (tot + pad > TCAP) sts32(sb + SM_FLAG, 1);
                sts32(sb + SM_CURS + lt * 4, (tile * TCAP + pad + pre) | (k << 20));
                if (k == 0) sts32(sb + SM_TCNT + tile * 4, tot);
            }
        } else if (lt >= 224) {
            sts32(sb + SM_CURS + (lt - 128) * 4, 16 * TCAP + lane);
        }
        lt_bar();
        TRACE(29);
        if (lds32(sb + SM_FLAG) == 0) {
#pragma unroll
            for (int m = 0; m < 6; m++) {
                if (any[m]) {
                    const uint32_t e0s = (uint32_t)(((m < 5) ? (lt >> 1) : pi5) * ECH) << 14;
                    uint32_t cur[3];
#pragma unroll
                    for (int s = 0; s < 3; s++) cur[s] = lds32(sb + SM_CURS + ao[3 * m + s]);
#pragma unroll
                    for (int s = 0; s < 3; s++) {
                        const uint32_t pl = (s == 0) ? pv[m].y : ((s == 1) ? pv[m].z : pv[m].w);
                        const uint32_t pos = (cur[s] & 0xFFFF) + ((nval[m] > s) ? rk[3 * m + s] : 0);
                        sts32(sb + SM_LSE + pos * 4, (pl & 0x3FFF) + ((pl >> 21) << 14) + e0s);
                        sts8(sb + SM_LID + pos, cur[s] >> 16);
                    }
                }
            }
            if (lt < 128) {
                const int tile = lt >> 3, sl = lt & 7;
                const int pad = (0 - (int)lds32(sb + SM_TCNT + tile * 4)) & 7;
                if (sl < pad) { sts8(sb + SM_LID + tile * TCAP + sl, 0x7F); sts32(sb + SM_LSE + (tile * TCAP + sl) * 4, 0); }
            }
        } else if (lt < NPC) {
            sts8(sb + SM_TNODE + (lt & 15) * 8 + (lt >> 4), lt);
        }
        TRACE(30);
    }
    TRACE(31);
    __syncthreads();
    TRACE(32);
    const bool slow = lds32(sb + SM_FLAG) != 0;

    const uint32_t ring0 = sb + SM_R0 + w * STAGE, ring1 = sb + SM_R1 + w * STAGE;
    const char* tab_l = p.table + lane * 16;
    asm volatile("" : "+l"(tab_l));
    const char* e_l = (const char*)p.e_attr + (lane & 1) * 16;
    asm volatile("" : "+l"(e_l));
    const uint32_t cp_off = lane * 16;
    const uint32_t ecp_off = 4096 + ((lane >> 1) & 7) * 32 + (((lane & 1) ^ ((lane >> 3) & 1)) << 4);
    const uint32_t lsrc = sb + SM_LSE + w * TCAP * 4, lid = sb + SM_LID + w * TCAP;
    const uint32_t leid = lsrc + ((lane >> 1) & 7) * 4;

    auto issue_full = [&](int it, uint32_t st) {
        const uint4 s0 = lds128(lsrc + it * 32), s1 = lds128(lsrc + it * 32 + 16);
        const uint32_t eo = lds32(leid + it * 32);
        const uint32_t sv[8] = {s0.x, s0.y, s0.z, s0.w, s1.x, s1.y, s1.z, s1.w};
        const uint32_t a = st + cp_off;
#pragma unroll
        for (int j = 0; j < 8; j++) cp16((a ^ (j << 4)) + j * 512, tab_l + (size_t)(sv[j] & 0x3FFF) * 512);
        if (lane < 16) cp16(st + ecp_off, e_l + (size_t)(eo >> 14) * 32);
    };
    auto issue0 = [&]() {
        const int cnt = lds32(sb + SM_TCNT + w * 4), nit = (cnt + 7) >> 3;
        if (nit > 0) {
            const int pad = nit * 8 - cnt;
            const uint4 s0 = lds128(lsrc), s1 = lds128(lsrc + 16);
            const uint32_t eo = lds32(leid);
            const uint32_t sv[8] = {s0.x, s0.y, s0.z, s0.w, s1.x, s1.y, s1.z, s1.w};
            const uint32_t a = ring0 + cp_off;
#pragma unroll
            for (int j = 0; j < 8; j++) cp16z((a ^ (j << 4)) + j * 512, tab_l + (size_t)(sv[j] & 0x3FFF) * 512, (j >= pad) ? 16 : 0);
            if (lane < 16) cp16z(ring0 + ecp_off, e_l + (size_t)(eo >> 14) * 32, (((lane >> 1) & 7) >= pad) ? 16 : 0);
        }
        cp_commit();
    };
    auto issue1 = [&]() {
        if ((int)lds32(sb + SM_TCNT + w * 4) > 8) issue_full(1, ring1);
        cp_commit();
    };
    if (!slow) {
        issue0();
        if (w >= 8) issue1();
    }
    TRACE(33);

    const int nslot = (w < 12) ? 5 : 4;
    const int mynode = lds8(sb + SM_TNODE + w * 8 + ((rr < nslot) ? rr : 0));
    uint32_t xAf[8][2];
    float agg[8][4];
    const uint32_t ident = (g == 2 * t) ? 0x3F80u : ((g == 2 * t + 1) ? 0x3F800000u : 0u);
    {
#pragma unroll
        for (int jp = 0; jp < 4; jp++) {
            const int c = 4 * jp + mi;
            const uint32_t off = (c >> 3) * 16384 + mynode * 128 + (((c & 7) ^ (mynode & 7)) << 4);
            uint32_t q[4];
            ldsm4t(q, sb + SM_WA + off);
            xAf[2 * jp][0] = q[0]; xAf[2 * jp][1] = q[1]; xAf[2 * jp + 1][0] = q[2]; xAf[2 * jp + 1][1] = q[3];
            ldsm4t(q, sb + SM_R1 + off);
            mma1688_z(agg[2 * jp], q[0], q[1], ident);
            mma1688_z(agg[2 * jp + 1], q[2], q[3], ident);
        }
    }
    if (w < 8) {
        asm volatile("bar.sync 4, 512;" ::: "memory");
        if (!slow) issue1();
    } else {
        asm volatile("bar.arrive 4, 512;" ::: "memory");
    }
    TRACE(34);

    const uint32_t ld_off = rr * 512 + ((mi ^ rr) << 4);
    const uint32_t eld_off = 4096 + rr * 32 + (((mi & 1) ^ ((rr >> 2) & 1)) << 4);
    const uint32_t selg = g | ((8 | g) << 4) | ((8 | g) << 8) | ((8 | g) << 12);
    const uint32_t selt = (2 * t) | ((8 | (2 * t)) << 4) | ((2 * t + 1) << 8) | ((8 | (2 * t + 1)) << 12);
    const uint32_t gg = (g * 16) | ((g * 16) << 16);

    const int nseg = slow ? NSEG : 1;
    for (int seg = 0; seg < nseg; seg++) {
        if (slow) {
            __syncthreads();
            if (tid < 16) sts32(sb + SM_TCNT + tid * 4, 0);
            __syncthreads();
            const int e = seg * TCAP + tid;
            int loc = -1; uint32_t r = 0;
            if (tid < TCAP && e < EE) {
                const int dd = __ldg(p.dst + e) - b * NPC;
                if (dd >= 0 && dd < NPC) { loc = dd; r = atoms_add(sb + SM_TCNT + (loc & 15) * 4, 1); }
            }
            __syncthreads();
            if (loc >= 0) {
                const uint32_t tile = loc & 15, tot = lds32(sb + SM_TCNT + tile * 4);
                const uint32_t pos = tile * TCAP + ((0u - tot) & 7u) + r;
                sts32(sb + SM_LSE + pos * 4, (uint32_t)__ldg(p.src + e) | ((uint32_t)e << 14));
                sts8(sb + SM_LID + pos, (loc >> 4) << 4);
            }
            const int pad = (0 - (int)lds32(sb + SM_TCNT + w * 4)) & 7;
            if (lane < pad) { sts8(sb + SM_LID + w * TCAP + lane, 0x7F); sts32(sb + SM_LSE + (w * TCAP + lane) * 4, 0); }
            __syncthreads();
            issue0();
            issue1();
        }
        const int nit = ((int)lds32(sb + SM_TCNT + w * 4) + 7) >> 3;
        for (int it = 0; it < nit; it++) {
            const uint32_t st = (it & 1) ? ring1 : ring0;
            if (it == 0) cp_wait<1>(); else cp_wait<0>();
            __syncwarp();
            if (it >= 1 && it + 1 < nit) issue_full(it + 1, (it & 1) ? ring0 : ring1);
            cp_commit();
            uint32_t eb[2];
            ldsm2(eb, st + eld_off);
            const uint2 iw = lds64(lid + it * 8);
            const uint32_t sx = shl_clamp(0x3F80u, prmt(iw.x, iw.y, selg) - 32 * t);
            const uint32_t sa = seteq_bf16x2(prmt(iw.x, iw.y, selt), gg);
            const uint32_t la0 = st + ld_off, la1 = la0 ^ 64;
#pragma unroll
            for (int jj = 0; jj < 4; jj++) {
                uint32_t xb[4], hv[4];
                const uint32_t la = ((jj & 1) ? la1 : la0) + (jj >> 1) * 128;
                ldsm4(xb, la);
                ldsm4t(hv, la + 256);
#pragma unroll
                for (int u = 0; u < 2; u++) {
                    const int j = 2 * jj + u;
                    float a[4];
                    mma16816_z(a, Cf[j][0], Cf[j][1], Cf[j][2], Cf[j][3], eb[0], eb[1]);
                    mma1688(a, xAf[j][0], xAf[j][1], sx);
                    mma16816(a, ident, 0u, 0u, ident, xb[2 * u], xb[2 * u + 1]);
                    const uint32_t m0 = fma_bf16x2(pack_bf16(tanh_ap(a[0]), tanh_ap(a[1])), hv[2 * u], hv[2 * u]);
                    const uint32_t m1 = fma_bf16x2(pack_bf16(tanh_ap(a[2]), tanh_ap(a[3])), hv[2 * u + 1], hv[2 * u + 1]);
                    mma1688(agg[j], m0, m1, sa);
                }
            }
        }
        cp_wait<0>();
        __syncwarp();
    }
    TRACE(35);

    {
        uint32_t o[8][2];
#pragma unroll
        for (int j = 0; j < 8; j++) {
            float v[4];
#pragma unroll
            for (int q = 0; q < 4; q++) { const float h = agg[j][q]; v[q] = fmaf(h, tanh_ap(h), h); }
            o[j][0] = pack_bf16(v[0], v[1]); o[j][1] = pack_bf16(v[2], v[3]);
        }
#pragma unroll
        for (int jp = 0; jp < 4; jp++) {
            const int c = 4 * jp + mi;
            stsm4t(ring0 + rr * 256 + ((c & 8) << 4) + (((c & 7) ^ rr) << 4), o[2 * jp][0], o[2 * jp][1], o[2 * jp + 1][0], o[2 * jp + 1][1]);
        }
        __syncwarp();
#pragma unroll
        for (int i = 0; i < 3; i++) {
            const int idx = lane + 32 * i, row = idx >> 4, c = idx & 15;
            const int nd = b * NPC + __shfl_sync(0xffffffffu, mynode, row & 7);
            if (row < nslot && nd < NN) {
                const uint4 v = lds128(ring0 + row * 256 + ((c & 8) << 4) + (((c & 7) ^ row) << 4));
                *(uint4*)((char*)p.out + (size_t)nd * 256 + c * 16) = v;
            }
        }
    }
    TRACE(36);
}

typedef CUresult (*EncodeFn)(CUtensorMap*, CUtensorMapDataType, cuuint32_t, void*, const cuuint64_t*, const cuuint64_t*,
                             const cuuint32_t*, const cuuint32_t*, CUtensorMapInterleave, CUtensorMapSwizzle,
                             CUtensorMapL2promotion, CUtensorMapFloatOOBfill);

static void make_map(EncodeFn enc, CUtensorMap* tm, const void* base, int rows, int cols, int box_rows) {
    cuuint64_t dims[2] = {(cuuint64_t)cols, (cuuint64_t)rows};
    cuuint64_t strides[1] = {(cuuint64_t)cols * 2};
    cuuint32_t box[2] = {64, (cuuint32_t)box_rows};
    cuuint32_t es[2] = {1, 1};
    enc(tm, CU_TENSOR_MAP_DATA_TYPE_BFLOAT16, 2, (void*)base, dims, strides, box, es, CU_TENSOR_MAP_INTERLEAVE_NONE,
        CU_TENSOR_MAP_SWIZZLE_128B, CU_TENSOR_MAP_L2_PROMOTION_NONE, CU_TENSOR_MAP_FLOAT_OOB_FILL_NONE);
}

}

extern "C" void kernel_launch(void* const* d_in, const int* in_sizes, int n_in, void* d_out, int out_size) {
    using namespace egc;
    (void)in_sizes; (void)n_in; (void)out_size;
    static EncodeFn enc = nullptr;
    static void* table = nullptr;
    static void* xch = nullptr;
    static void* bar = nullptr;
    if (!enc) {
        void* fn = nullptr;
        cudaDriverEntryPointQueryResult qr;
        cudaGetDriverEntryPoint("cuTensorMapEncodeTiled", &fn, cudaEnableDefault, &qr);
        enc = (EncodeFn)fn;
        cudaGetSymbolAddress(&table, g_table);
        cudaGetSymbolAddress(&xch, g_xch);
        cudaGetSymbolAddress(&bar, g_bar);
        cudaFuncSetAttribute(egc_kernel, cudaFuncAttributeMaxDynamicSharedMemorySize, SMEM_BYTES);
    }
    CUtensorMap tm_x, tm_g, tm_u, tm_v, tm_t;
    make_map(enc, &tm_x, d_in[0], NN, 128, 80);
    make_map(enc, &tm_u, d_in[4], 128, 128, 128);
    make_map(enc, &tm_v, d_in[5], 128, 128, 128);
    make_map(enc, &tm_g, d_in[6], 272, 128, 128);
    make_map(enc, &tm_t, table, NN, 256, NPC);
    Params p;
    p.e_attr = (const bf16*)d_in[1];
    p.src = (const int*)d_in[2];
    p.dst = (const int*)d_in[3];
    p.gw = (const bf16*)d_in[6];
    p.out = (bf16*)d_out;
    p.bar = (unsigned*)bar;
    p.xch = (uint4*)xch;
    p.table = (const char*)table;
    egc_kernel<<<NCTA, NTHR, SMEM_BYTES, cudaStreamPerThread>>>(p, tm_x, tm_g, tm_u, tm_v, tm_t);
}
```

```cpp
#include <cuda_runtime.h>
#include <cuda_bf16.h>
#include <cuda.h>
#include <stdint.h>
#include <type_traits>

#define PIPE 0

namespace egc {

typedef __nv_bfloat16 bf16;

constexpr int NN = 10000, EE = 160000;
constexpr int NCTA = 132, NPC = 76, ECH = 1216, NTHR = 512;
constexpr int PIECES = 10, XCAP = 3 * PIECES;
constexpr int TCAP = 96;
constexpr int NSEG = (EE + TCAP - 1) / TCAP;

constexpr int STAGE = 4352;
constexpr int SM_R0 = 0;
constexpr int SM_R1 = 16 * STAGE;
constexpr int SM_S = SM_R1;
constexpr int SM_WU = SM_R1 + 8 * STAGE;
constexpr int SM_WA = SM_R1 + 16 * STAGE;
constexpr int SM_X = SM_WA + 32768;
constexpr int SM_C = SM_X + 20480;
constexpr int SM_LSE = SM_C + 4096;
constexpr int SM_LID = SM_LSE + 6144 + 128;
constexpr int SM_HIST = SM_LID + 1536 + 32;
constexpr int SM_KEYS = SM_HIST + 544;
constexpr int SM_CURS = SM_KEYS + 512;
constexpr int SM_DBIN = SM_CURS + 512;
constexpr int SM_TDEG = SM_DBIN + 256;
constexpr int SM_TNODE = SM_TDEG + 512;
constexpr int SM_TCNT = SM_TNODE + 128;
constexpr int SM_FLAG = SM_TCNT + 64;
constexpr int NCAP = 40;
constexpr int SM_NL = SM_FLAG + 16;
constexpr int SM_BAR = SM_NL + NPC * NCAP * 4 + 128;
constexpr int SM_TRACE = SM_BAR + 9 * 8 + 8;
constexpr int SM_END = SM_TRACE + 2 * 48 * 4;
constexpr int SMEM_BYTES = SM_END + 1024;

__device__ __align__(1024) uint4 g_table[NN * 32];
__device__ __align__(1024) uint4 g_xch[NCTA * NCTA * PIECES];
__device__ __align__(128) unsigned g_bar[32];
#define TRACE(i) do {} while (0)

__device__ __forceinline__ void mma16816(float* d, uint32_t a0, uint32_t a1, uint32_t a2, uint32_t a3, uint32_t b0, uint32_t b1) {
    asm("mma.sync.aligned.m16n8k16.row.col.f32.bf16.bf16.f32 {%0,%1,%2,%3}, {%4,%5,%6,%7}, {%8,%9}, {%0,%1,%2,%3};"
        : "+f"(d[0]), "+f"(d[1]), "+f"(d[2]), "+f"(d[3]) : "r"(a0), "r"(a1), "r"(a2), "r"(a3), "r"(b0), "r"(b1));
}
__device__ __forceinline__ void mma16816_z(float* d, uint32_t a0, uint32_t a1, uint32_t a2, uint32_t a3, uint32_t b0, uint32_t b1) {
    asm("mma.sync.aligned.m16n8k16.row.col.f32.bf16.bf16.f32 {%0,%1,%2,%3}, {%4,%5,%6,%7}, {%8,%9}, {%10,%10,%10,%10};"
        : "=f"(d[0]), "=f"(d[1]), "=f"(d[2]), "=f"(d[3]) : "r"(a0), "r"(a1), "r"(a2), "r"(a3), "r"(b0), "r"(b1), "f"(0.f));
}
__device__ __forceinline__ void mma1688(float* d, uint32_t a0, uint32_t a1, uint32_t b0) {
    asm("mma.sync.aligned.m16n8k8.row.col.f32.bf16.bf16.f32 {%0,%1,%2,%3}, {%4,%5}, {%6}, {%0,%1,%2,%3};"
        : "+f"(d[0]), "+f"(d[1]), "+f"(d[2]), "+f"(d[3]) : "r"(a0), "r"(a1), "r"(b0));
}
__device__ __forceinline__ void mma1688_z(float* d, uint32_t a0, uint32_t a1, uint32_t b0) {
    asm("mma.sync.aligned.m16n8k8.row.col.f32.bf16.bf16.f32 {%0,%1,%2,%3}, {%4,%5}, {%6}, {%7,%7,%7,%7};"
        : "=f"(d[0]), "=f"(d[1]), "=f"(d[2]), "=f"(d[3]) : "r"(a0), "r"(a1), "r"(b0), "f"(0.f));
}
__device__ __forceinline__ void ldsm4(uint32_t* r, uint32_t addr) {
    asm volatile("ldmatrix.sync.aligned.m8n8.x4.shared.b16 {%0,%1,%2,%3}, [%4];" : "=r"(r[0]), "=r"(r[1]), "=r"(r[2]), "=r"(r[3]) : "r"(addr) : "memory");
}
__device__ __forceinline__ void ldsm4t(uint32_t* r, uint32_t addr) {
    asm volatile("ldmatrix.sync.aligned.m8n8.x4.trans.shared.b16 {%0,%1,%2,%3}, [%4];" : "=r"(r[0]), "=r"(r[1]), "=r"(r[2]), "=r"(r[3]) : "r"(addr) : "memory");
}
__device__ __forceinline__ void ldsm2(uint32_t* r, uint32_t addr) {
    asm volatile("ldmatrix.sync.aligned.m8n8.x2.shared.b16 {%0,%1}, [%2];" : "=r"(r[0]), "=r"(r[1]) : "r"(addr) : "memory");
}
__device__ __forceinline__ void stsm4t(uint32_t addr, uint32_t r0, uint32_t r1, uint32_t r2, uint32_t r3) {
    asm volatile("stmatrix.sync.aligned.m8n8.x4.trans.shared.b16 [%0], {%1,%2,%3,%4};" :: "r"(addr), "r"(r0), "r"(r1), "r"(r2), "r"(r3) : "memory");
}
__device__ __forceinline__ float tanh_ap(float x) { float r; asm("tanh.approx.f32 %0, %1;" : "=f"(r) : "f"(x)); return r; }
__device__ __forceinline__ uint32_t pack_bf16(float lo, float hi) { uint32_t r; asm("cvt.rn.bf16x2.f32 %0, %1, %2;" : "=r"(r) : "f"(hi), "f"(lo)); return r; }
__device__ __forceinline__ uint32_t fma_bf16x2(uint32_t a, uint32_t b, uint32_t c) { uint32_t r; asm("fma.rn.bf16x2 %0, %1, %2, %3;" : "=r"(r) : "r"(a), "r"(b), "r"(c)); return r; }
__device__ __forceinline__ uint32_t mul_bf16x2(uint32_t a, uint32_t b) { uint32_t r; asm("mul.rn.bf16x2 %0, %1, %2;" : "=r"(r) : "r"(a), "r"(b)); return r; }
__device__ __forceinline__ uint32_t seteq_bf16x2(uint32_t a, uint32_t b) { uint32_t r; asm("set.eq.bf16x2.bf16x2 %0, %1, %2;" : "=r"(r) : "r"(a), "r"(b)); return r; }
__device__ __forceinline__ uint32_t prmt(uint32_t a, uint32_t b, uint32_t s) { uint32_t r; asm("prmt.b32 %0, %1, %2, %3;" : "=r"(r) : "r"(a), "r"(b), "r"(s)); return r; }
__device__ __forceinline__ uint32_t shl_clamp(uint32_t a, uint32_t s) { uint32_t r; asm("shl.b32 %0, %1, %2;" : "=r"(r) : "r"(a), "r"(s)); return r; }
__device__ __forceinline__ void cp16(uint32_t dst, const void* src) { asm volatile("cp.async.cg.shared.global [%0], [%1], 16;" :: "r"(dst), "l"(src) : "memory"); }
__device__ __forceinline__ void cp16z(uint32_t dst, const void* src, uint32_t sz) { asm volatile("cp.async.cg.shared.global [%0], [%1], 16, %2;" :: "r"(dst), "l"(src), "r"(sz) : "memory"); }
__device__ __forceinline__ const void* madw(uint32_t a, uint32_t m, const void* base) {
    const void* r; asm("mad.wide.u32 %0, %1, %2, %3;" : "=l"(r) : "r"(a), "r"(m), "l"(base)); return r;
}
__device__ __forceinline__ void cp16_p(bool p, uint32_t dst, const void* src) {
    asm volatile("{\n.reg .pred p;\nsetp.ne.u32 p, %2, 0;\n@p cp.async.cg.shared.global [%0], [%1], 16;\n}" :: "r"(dst), "l"(src), "r"((uint32_t)p) : "memory");
}
__device__ __forceinline__ void cp_commit() { asm volatile("cp.async.commit_group;" ::: "memory"); }
template <int N> __device__ __forceinline__ void cp_wait() { asm volatile("cp.async.wait_group %0;" :: "n"(N) : "memory"); }
__device__ __forceinline__ uint4 lds128(uint32_t a) { uint4 v; asm volatile("ld.shared.v4.u32 {%0,%1,%2,%3}, [%4];" : "=r"(v.x), "=r"(v.y), "=r"(v.z), "=r"(v.w) : "r"(a) : "memory"); return v; }
__device__ __forceinline__ uint2 lds64(uint32_t a) { uint2 v; asm volatile("ld.shared.v2.u32 {%0,%1}, [%2];" : "=r"(v.x), "=r"(v.y) : "r"(a) : "memory"); return v; }
__device__ __forceinline__ uint32_t lds32(uint32_t a) { uint32_t v; asm volatile("ld.shared.u32 %0, [%1];" : "=r"(v) : "r"(a) : "memory"); return v; }
__device__ __forceinline__ uint32_t lds8(uint32_t a) { uint32_t v; asm volatile("ld.shared.u8 %0, [%1];" : "=r"(v) : "r"(a) : "memory"); return v; }
__device__ __forceinline__ void sts32(uint32_t a, uint32_t v) { asm volatile("st.shared.u32 [%0], %1;" :: "r"(a), "r"(v) : "memory"); }
__device__ __forceinline__ void sts8(uint32_t a, uint32_t v) { asm volatile("st.shared.u8 [%0], %1;" :: "r"(a), "r"(v) : "memory"); }
__device__ __forceinline__ void sts128(uint32_t a, uint4 v) { asm volatile("st.shared.v4.u32 [%0], {%1,%2,%3,%4};" :: "r"(a), "r"(v.x), "r"(v.y), "r"(v.z), "r"(v.w) : "memory"); }
__device__ __forceinline__ uint32_t atoms_add(uint32_t a, uint32_t v) { uint32_t r; asm volatile("atom.shared.add.u32 %0, [%1], %2;" : "=r"(r) : "r"(a), "r"(v) : "memory"); return r; }
__device__ __forceinline__ void reds_add(uint32_t a, uint32_t v) { asm volatile("red.shared.add.u32 [%0], %1;" :: "r"(a), "r"(v) : "memory"); }
__device__ __forceinline__ uint32_t atoms_add_p(bool p, uint32_t a, uint32_t v) {
    uint32_t r = 0;
    asm volatile("{\n.reg .pred p;\nsetp.ne.u32 p, %3, 0;\n@p atom.shared.add.u32 %0, [%1], %2;\n}" : "+r"(r) : "r"(a), "r"(v), "r"((uint32_t)p) : "memory");
    return r;
}
__device__ __forceinline__ uint32_t lds32_p(bool p, uint32_t a) {
    uint32_t r = 0;
    asm volatile("{\n.reg .pred p;\nsetp.ne.u32 p, %2, 0;\n@p ld.shared.u32 %0, [%1];\n}" : "+r"(r) : "r"(a), "r"((uint32_t)p) : "memory");
    return r;
}
__device__ __forceinline__ void sts32_p(bool p, uint32_t a, uint32_t v) {
    asm volatile("{\n.reg .pred p;\nsetp.ne.u32 p, %2, 0;\n@p st.shared.u32 [%0], %1;\n}" :: "r"(a), "r"(v), "r"((uint32_t)p) : "memory");
}
__device__ __forceinline__ void sts8_p(bool p, uint32_t a, uint32_t v) {
    asm volatile("{\n.reg .pred p;\nsetp.ne.u32 p, %2, 0;\n@p st.shared.u8 [%0], %1;\n}" :: "r"(a), "r"(v), "r"((uint32_t)p) : "memory");
}
__device__ __forceinline__ void st_piece(uint4* p, uint4 v) {
    asm volatile("{\n.reg .b128 q;\n.reg .b64 lo, hi;\nmov.b64 lo, {%1,%2};\nmov.b64 hi, {%3,%4};\nmov.b128 q, {lo, hi};\nst.relaxed.gpu.global.b128 [%0], q;\n}"
                 :: "l"(p), "r"(v.x), "r"(v.y), "r"(v.z), "r"(v.w) : "memory");
}
__device__ __forceinline__ uint4 ld_piece(const uint4* p) {
    uint4 v;
    asm volatile("{\n.reg .b128 q;\n.reg .b64 lo, hi;\nld.relaxed.gpu.global.b128 q, [%4];\nmov.b128 {lo, hi}, q;\nmov.b64 {%0,%1}, lo;\nmov.b64 {%2,%3}, hi;\n}"
                 : "=r"(v.x), "=r"(v.y), "=r"(v.z), "=r"(v.w) : "l"(p) : "memory");
    return v;
}
__device__ __forceinline__ void mbar_init(uint32_t bar, uint32_t cnt) { asm volatile("mbarrier.init.shared::cta.b64 [%0], %1;" :: "r"(bar), "r"(cnt) : "memory"); }
__device__ __forceinline__ void mbar_expect(uint32_t bar, uint32_t bytes) { asm volatile("mbarrier.arrive.expect_tx.shared::cta.b64 _, [%0], %1;" :: "r"(bar), "r"(bytes) : "memory"); }
__device__ __forceinline__ void mbar_wait(uint32_t bar, uint32_t parity) {
    uint32_t ok; int it = 0;
    do {
        asm volatile("{\n.reg .pred p;\nmbarrier.try_wait.parity.shared::cta.b64 p, [%1], %2;\nselp.u32 %0, 1, 0, p;\n}" : "=r"(ok) : "r"(bar), "r"(parity) : "memory");
    } while (!ok && ++it < (1 << 22));
}
__device__ __forceinline__ void tma_load2d(uint32_t dst, const CUtensorMap* tm, int c0, int c1, uint32_t bar) {
    asm volatile("cp.async.bulk.tensor.2d.shared::cluster.global.mbarrier::complete_tx::bytes [%0], [%1, {%3, %4}], [%2];"
                 :: "r"(dst), "l"(tm), "r"(bar), "r"(c0), "r"(c1) : "memory");
}
__device__ __forceinline__ void tma_load2d_mc(uint32_t dst, const CUtensorMap* tm, int c0, int c1, uint32_t bar) {
    asm volatile("cp.async.bulk.tensor.2d.shared::cluster.global.mbarrier::complete_tx::bytes.multicast::cluster [%0], [%1, {%3, %4}], [%2], %5;"
                 :: "r"(dst), "l"(tm), "r"(bar), "r"(c0), "r"(c1), "h"((uint16_t)3) : "memory");
}
__device__ __forceinline__ void tma_store2d(const CUtensorMap* tm, int c0, int c1, uint32_t src) {
    asm volatile("cp.async.bulk.tensor.2d.global.shared::cta.bulk_group [%0, {%2, %3}], [%1];"
                 :: "l"(tm), "r"(src), "r"(c0), "r"(c1) : "memory");
}
__device__ __forceinline__ void lt_bar() { asm volatile("bar.sync 3, 256;" ::: "memory"); }
__device__ __forceinline__ void wg_bar(int id) { asm volatile("bar.sync %0, 128;" :: "r"(id) : "memory"); }

__device__ __forceinline__ void wgmma_n80(float (&d)[40], uint64_t da, uint64_t db, int acc) {
    asm volatile("{\n.reg .pred p;\nsetp.ne.b32 p, %42, 0;\n"
        "wgmma.mma_async.sync.aligned.m64n80k16.f32.bf16.bf16 "
        "{%0,%1,%2,%3,%4,%5,%6,%7,%8,%9,%10,%11,%12,%13,%14,%15,%16,%17,%18,%19,"
        "%20,%21,%22,%23,%24,%25,%26,%27,%28,%29,%30,%31,%32,%33,%34,%35,%36,%37,%38,%39}, "
        "%40, %41, p, 1, 1, 1, 0;\n}\n"
        : "+f"(d[0]), "+f"(d[1]), "+f"(d[2]), "+f"(d[3]), "+f"(d[4]), "+f"(d[5]), "+f"(d[6]), "+f"(d[7]), "+f"(d[8]), "+f"(d[9]),
          "+f"(d[10]), "+f"(d[11]), "+f"(d[12]), "+f"(d[13]), "+f"(d[14]), "+f"(d[15]), "+f"(d[16]), "+f"(d[17]), "+f"(d[18]), "+f"(d[19]),
          "+f"(d[20]), "+f"(d[21]), "+f"(d[22]), "+f"(d[23]), "+f"(d[24]), "+f"(d[25]), "+f"(d[26]), "+f"(d[27]), "+f"(d[28]), "+f"(d[29]),
          "+f"(d[30]), "+f"(d[31]), "+f"(d[32]), "+f"(d[33]), "+f"(d[34]), "+f"(d[35]), "+f"(d[36]), "+f"(d[37]), "+f"(d[38]), "+f"(d[39])
        : "l"(da), "l"(db), "r"(acc));
}

__device__ __forceinline__ void gemm_issue(float (&d)[40], uint32_t wbase, uint32_t xbase) {
    asm volatile("wgmma.fence.sync.aligned;" ::: "memory");
#pragma unroll
    for (int s = 0; s < 8; s++) {
        const uint32_t aa = wbase + s * 2048, ab = xbase + (s >> 2) * 10240 + (s & 3) * 32;
        const uint64_t da = (uint64_t)((aa & 0x3FFFF) >> 4) | ((uint64_t)64 << 16) | ((uint64_t)64 << 32) | ((uint64_t)1 << 62);
        const uint64_t db = (uint64_t)((ab & 0x3FFFF) >> 4) | ((uint64_t)1 << 16) | ((uint64_t)64 << 32) | ((uint64_t)1 << 62);
        wgmma_n80(d, da, db, s > 0);
    }
    asm volatile("wgmma.commit_group.sync.aligned;" ::: "memory");
}
__device__ __forceinline__ void gemm_wait(float (&d)[40]) {
    asm volatile("wgmma.wait_group.sync.aligned 0;" ::: "memory");
#pragma unroll
    for (int i = 0; i < 40; i++) asm volatile("" : "+f"(d[i]) :: "memory");
}
__device__ __forceinline__ void gemm_store(const float (&d)[40], float sc, uint32_t base, int w4, int lane) {
    const int mi = lane >> 3, rr = lane & 7;
    const uint32_t sa = base + (rr + 8 * (mi >> 1)) * 128 + (((2 * w4 + (mi & 1)) ^ rr) << 4);
#pragma unroll
    for (int p = 0; p < 5; p++) {
        const float* q = d + 8 * p;
        stsm4t(sa + p * 2048, pack_bf16(q[0] * sc, q[1] * sc), pack_bf16(q[2] * sc, q[3] * sc),
               pack_bf16(q[4] * sc, q[5] * sc), pack_bf16(q[6] * sc, q[7] * sc));
    }
}

struct Params {
    const int* dst;
    const int* src;
    unsigned* bar;
    uint4* xch;
    const bf16* gw;
    const bf16* e_attr;
    const char* table;
    bf16* out;
};

__global__ void __launch_bounds__(NTHR, 1)
egc_kernel(const Params p, const __grid_constant__ CUtensorMap tm_x, const __grid_constant__ CUtensorMap tm_g,
           const __grid_constant__ CUtensorMap tm_u, const __grid_constant__ CUtensorMap tm_v, const __grid_constant__ CUtensorMap tm_t) {
    extern __shared__ unsigned char smem_raw[];
    const uint32_t sb = ((uint32_t)__cvta_generic_to_shared(smem_raw) + 1023u) & ~1023u;
    const int tid = threadIdx.x, lane = tid & 31, b = blockIdx.x;
    const int w = __shfl_sync(0xffffffffu, tid >> 5, 0);
    const int wq = w >> 2, w4 = w & 3;
    const int g = lane >> 2, t = lane & 3, mi = lane >> 3, rr = lane & 7;
    TRACE(0);

    uint32_t Cf[8][4];
    auto load_cf = [&]() {
        const int krow = rr + 8 * (mi >> 1);
#pragma unroll
        for (int j = 0; j < 8; j++) {
            const int c = 2 * j + (mi & 1);
            ldsm4t(Cf[j], sb + SM_C + krow * 256 + ((c & 8) << 4) + (((c & 7) ^ rr) << 4));
#pragma unroll
            for (int q = 0; q < 4; q++) Cf[j][q] = mul_bf16x2(Cf[j][q], 0x3F003F00u);
        }
    };
    uint32_t xAf[8][2];
    float agg[8][4];
    const uint32_t ident = (g == 2 * t) ? 0x3F80u : ((g == 2 * t + 1) ? 0x3F800000u : 0u);
    const int nslot = (w < 12) ? 5 : 4;
    auto load_node_frags = [&]() {
        const int mynode = lds8(sb + SM_TNODE + w * 8 + ((rr < nslot) ? rr : 0));
#pragma unroll
        for (int jp = 0; jp < 4; jp++) {
            const int c = 4 * jp + mi;
            const uint32_t off = mynode * 128 + (((c & 7) ^ (mynode & 7)) << 4);
            uint32_t q[4];
            ldsm4t(q, sb + SM_WA + (c >> 3) * 16384 + off);
            xAf[2 * jp][0] = q[0]; xAf[2 * jp][1] = q[1]; xAf[2 * jp + 1][0] = q[2]; xAf[2 * jp + 1][1] = q[3];
            ldsm4t(q, sb + SM_X + (c >> 3) * 10240 + off);
            mma1688_z(agg[2 * jp], q[0], q[1], ident);
            mma1688_z(agg[2 * jp + 1], q[2], q[3], ident);
        }
    };
    uint32_t bar_target = 0;
    constexpr int LT = 256;
    if (wq < 2) {
        uint32_t epoch = 0;
        {
            const int r = tid >> 4, c = tid & 15;
            cp16(sb + SM_C + r * 256 + ((c & 8) << 4) + (((c & 7) ^ (r & 7)) << 4), p.gw + (256 + r) * 128 + c * 8);
            cp_commit();
        }
        if (tid == 0) {
            asm volatile("ld.relaxed.gpu.global.u32 %0, [%1];" : "=r"(epoch) : "l"(p.bar) : "memory");
            for (int i = 0; i < 9; i++) mbar_init(sb + SM_BAR + i * 8, 1);
            asm volatile("fence.mbarrier_init.release.cluster;" ::: "memory");
            const uint32_t bx = sb + SM_BAR;
            mbar_expect(bx, 20480);
#pragma unroll
            for (int i = 0; i < 8; i++) mbar_expect(bx + 8 + i * 8, 16384);
#define START_DELAY 700
            if (START_DELAY > 0) { uint32_t c0, c1; asm volatile("mov.u32 %0, %%clock;" : "=r"(c0)); do { asm volatile("mov.u32 %0, %%clock;" : "=r"(c1)); } while (c1 - c0 < START_DELAY); }
            tma_load2d(sb + SM_X, &tm_x, 0, b * NPC, bx);
            tma_load2d(sb + SM_X + 10240, &tm_x, 64, b * NPC, bx);
            tma_load2d(sb + SM_R0, &tm_g, 0, 128, bx + 8);
            tma_load2d(sb + SM_R0 + 16384, &tm_g, 64, 128, bx + 16);
            tma_load2d(sb + SM_R0 + 2 * 16384, &tm_v, 0, 0, bx + 24);
            tma_load2d(sb + SM_R0 + 3 * 16384, &tm_v, 64, 0, bx + 32);
        }
        cp_wait<0>();
        asm volatile("bar.sync 6, 256;" ::: "memory");
        asm volatile("bar.arrive 8, 512;" ::: "memory");
        TRACE(1);
        load_cf();
        float d[40];
        const uint32_t xt = sb + SM_X;
        const bool elect = (w4 == 0 && lane == 0);
        mbar_wait(sb + SM_BAR, 0);
#pragma unroll 1
        for (int r = 0; r < 4; r++) {
            const uint32_t wt = sb + ((r < 2) ? SM_R0 + r * 32768 : ((r == 2) ? SM_WA : SM_WU)) + wq * 16384;
            mbar_wait(sb + SM_BAR + 8 + (2 * r + wq) * 8, 0);
            TRACE(2 + 2 * r);
            gemm_issue(d, wt, xt);
            if (r == 0 && tid == 0) {
#pragma unroll
                for (int i = 0; i < 2; i++) {
                    tma_load2d(sb + SM_WA + i * 16384, &tm_g, i * 64, 0, sb + SM_BAR + 8 + (4 + i) * 8);
                    tma_load2d(sb + SM_WU + i * 16384, &tm_u, i * 64, 0, sb + SM_BAR + 8 + (6 + i) * 8);
                }
            }
#define FLAG_R 2
            if (r == FLAG_R) {
                asm volatile("bar.sync 4, 512;" ::: "memory");
                if (elect) {
                    asm volatile("cp.async.bulk.wait_group 0;" ::: "memory");
                    asm volatile("fence.proxy.async.global;" ::: "memory");
                    asm volatile("red.relaxed.gpu.global.add.u32 [%0], 1;" :: "l"(p.bar) : "memory");
                }
            }
            if (r == 3 && tid == 0) {
                const int e0 = b * ECH, ne = min(ECH, EE - e0);
                asm volatile("cp.async.bulk.prefetch.L2.global [%0], %1;" :: "l"(p.e_attr + (size_t)e0 * 16), "r"(ne * 32) : "memory");
            }
            __syncwarp();
            gemm_wait(d);
            if (r < 3) wg_bar(1 + wq); else asm volatile("bar.sync 6, 256;" ::: "memory");
            gemm_store(d, (r == 1) ? 0.25f : 0.5f, (r < 3) ? wt : xt + wq * 10240, w4, lane);
            if (r < 2) {
                asm volatile("fence.proxy.async.shared::cta;" ::: "memory");
                wg_bar(1 + wq);
                if (elect) {
                    tma_store2d(&tm_t, (2 * r + wq) * 64, b * NPC, wt);
                    asm volatile("cp.async.bulk.commit_group;" ::: "memory");
                }
                __syncwarp();
            }
            TRACE(3 + 2 * r);
        }

        bar_target = (epoch / (2 * NCTA) + 1) * (2 * NCTA);
        TRACE(9);
    } else {
        const int lt = tid - LT;
        int ed[5], es[5];
        uint32_t epoch;
#pragma unroll
        for (int m = 0; m < 5; m++) {
            const int k = lt + m * LT, e = b * ECH + k;
            ed[m] = ((k < ECH) && (e < EE)) ? __ldg(p.dst + e) : -1;
        }
#pragma unroll
        for (int m = 0; m < 5; m++) {
            const int k = lt + m * LT, e = b * ECH + k;
            es[m] = ((k < ECH) && (e < EE)) ? __ldg(p.src + e) : 0;
        }
        asm volatile("ld.relaxed.gpu.global.u32 %0, [%1];" : "=r"(epoch) : "l"(p.bar) : "memory");
        if (lt < 136) sts32(sb + SM_HIST + lt * 4, 0);
        if (lt < 128) { sts32(sb + SM_KEYS + lt * 4, 0); sts32(sb + SM_TDEG + lt * 4, 0); }
        if (lt < 64) sts32(sb + SM_DBIN + lt * 4, 0);
        if (lt == 0) sts32(sb + SM_FLAG, 0);
        lt_bar();
        TRACE(24);
        {
            uint32_t jj[5], rk[5];
#pragma unroll
            for (int m = 0; m < 5; m++) {
                jj[m] = (ed[m] >= 0) ? (((uint32_t)ed[m] * 55189u) >> 22) : (132 + (lane & 3));
                rk[m] = atoms_add(sb + SM_HIST + jj[m] * 4, 1);
            }
#pragma unroll
            for (int m = 0; m < 5; m++) {
                const uint32_t loc = (uint32_t)ed[m] - jj[m] * NPC;
                const uint32_t q = (rk[m] * 43691u) >> 17;
                const uint32_t off = jj[m] * (PIECES * 16) + q * 16 + (rk[m] - 3 * q + 1) * 4;
                sts32(sb + SM_S + ((ed[m] >= 0 && rk[m] < XCAP) ? off : NCTA * PIECES * 16 + lane * 4),
                      (uint32_t)es[m] | (loc << 14) | ((uint32_t)(lt + m * LT) << 21));
            }
        }
        const uint32_t bar_q = epoch / (2 * NCTA);
        epoch = (bar_q + 1) & 0xFFFFFF;
        TRACE(25);
        lt_bar();
        {
            uint4 v[6]; uint32_t c[6];
#pragma unroll
            for (int m = 0; m < 6; m++) {
                const int pc = min(lt + m * LT, NCTA * PIECES - 1);
                v[m] = lds128(sb + SM_S + pc * 16);
                c[m] = lds32(sb + SM_HIST + ((pc * 6554) >> 16) * 4);
            }
#pragma unroll
            for (int m = 0; m < 6; m++) {
                const int pc = lt + m * LT;
                const int j = (pc * 6554) >> 16, q = pc - j * PIECES;
                if ((m < 5 || pc < NCTA * PIECES) && (q < 4 || c[m] > 3 * (q & ~1) || b >= 128)) {
                    v[m].x = (epoch << 8) | min(c[m], 255u);
                    st_piece(p.xch + (((j * (PIECES / 2) + (q >> 1)) * NCTA + b) * 2 + (q & 1)), v[m]);
                }
            }
        }
        TRACE(46);
        asm volatile("bar.arrive 4, 512;" ::: "memory");
        lt_bar();
        if (lt == 0) asm volatile("red.relaxed.gpu.global.add.u32 [%0], 1;" :: "l"(p.bar + 1) : "memory");
        asm volatile("bar.sync 8, 512;" ::: "memory");
        load_cf();
        if (lt == 0) {
            uint32_t v; int it = 0;
            const uint32_t target = (bar_q + 1) * NCTA;
            do { asm volatile("ld.relaxed.gpu.global.u32 %0, [%1];" : "=r"(v) : "l"(p.bar + 1) : "memory"); }
            while ((int)(v - target) < 0 && ++it < (1 << 20));
        }
        lt_bar();
        TRACE(26);
        uint4 pv[6];
        const int pi5 = 128 + ((lt >> 1) & 3), pq5 = 2 * (lt >> 3) + (lt & 1);
        const uint4* px0 = p.xch + b * (NCTA * PIECES) + lt;
        const uint4* px5 = p.xch + b * (NCTA * PIECES) + (lt >> 3) * (2 * NCTA) + 256 + (lt & 7);
        const uint32_t tg = epoch << 8;
        auto fetch = [&](const uint4* a) {
            uint4 v = ld_piece(a);
            int it = 0;
            while (((v.x ^ tg) >> 8) && ++it < (1 << 20)) v = ld_piece(a);
            return v;
        };
        pv[0] = ld_piece(px0);
        pv[1] = ld_piece(px0 + 2 * NCTA);
        pv[5] = (lt < 4 * PIECES) ? ld_piece(px5) : make_uint4(tg, 0, 0, 0);
        if (((pv[0].x ^ tg) | (pv[1].x ^ tg) | (pv[5].x ^ tg)) >> 8) {
            pv[0] = fetch(px0); pv[1] = fetch(px0 + 2 * NCTA);
            if (lt < 4 * PIECES) pv[5] = fetch(px5);
        }
        const int cnt = pv[0].x & 255, cnt5 = pv[5].x & 255;
#pragma unroll
        for (int m = 2; m < 5; m++) pv[m] = (cnt > 6 * m) ? ld_piece(px0 + m * (2 * NCTA)) : make_uint4(tg, 0, 0, 0);
        if (cnt > XCAP || cnt5 > XCAP) sts32(sb + SM_FLAG, 1);
        TRACE(27);
        const uint32_t dmy = (96 + lane) * 4;
        auto place = [&](int m) {
            const int nv = (m < 5) ? cnt - 3 * (2 * m + (lt & 1)) : cnt5 - 3 * pq5;
            if (m < 2 || __any_sync(0xffffffffu, nv > 0)) {
                const uint32_t e0s = (uint32_t)(((m < 5) ? (lt >> 1) : pi5) * ECH) << 14;
                uint32_t ao[3], rk[3];
#pragma unroll
                for (int s = 0; s < 3; s++) {
                    const uint32_t pl = (s == 0) ? pv[m].y : ((s == 1) ? pv[m].z : pv[m].w);
                    ao[s] = (nv > s) ? ((pl >> 12) & 0x1FC) : dmy;
                    rk[s] = atoms_add(sb + SM_KEYS + ao[s], 1);
                }
#pragma unroll
                for (int s = 0; s < 3; s++) {
                    const uint32_t pl = (s == 0) ? pv[m].y : ((s == 1) ? pv[m].z : pv[m].w);
                    const bool ok = nv > s && rk[s] < NCAP;
                    sts32(sb + SM_NL + (ok ? ao[s] * NCAP + rk[s] * 4 : NPC * NCAP * 4 + lane * 4), (pl & 0x3FFF) + ((pl >> 21) << 14) + e0s);
                }
            }
        };
        place(0);
        place(1);
        place(5);
        if (((pv[2].x ^ tg) | (pv[3].x ^ tg) | (pv[4].x ^ tg)) >> 8) {
#pragma unroll
            for (int m = 2; m < 5; m++) if (cnt > 6 * m) pv[m] = fetch(px0 + m * (2 * NCTA));
        }
        place(2);
        place(3);
        place(4);
        TRACE(28);
        lt_bar();
        if (lt < 96) {
            const uint32_t deg = (lt < NPC) ? lds32(sb + SM_KEYS + lt * 4) : 0;
            const uint32_t bin = 63 - min(deg, 63u);
            const uint32_t r0 = atoms_add_p(lt < NPC, sb + SM_DBIN + bin * 4, 1);
            if (deg > NCAP) sts32(sb + SM_FLAG, 1);
            asm volatile("bar.sync 5, 96;" ::: "memory");
            const uint2 c2 = lds64(sb + SM_DBIN + lane * 8);
            uint32_t inc = c2.x + c2.y;
#pragma unroll
            for (int o = 1; o < 32; o <<= 1) { const uint32_t u = __shfl_up_sync(0xffffffffu, inc, o); if (lane >= o) inc += u; }
            const uint32_t ex = inc - c2.x - c2.y;
            const uint32_t pe = __shfl_sync(0xffffffffu, ex, bin >> 1), p0 = __shfl_sync(0xffffffffu, c2.x, bin >> 1);
            const int rank = pe + ((bin & 1) ? p0 : 0) + r0;
            const int k = rank >> 4, pos = rank & 15;
            const int tile = (k == 4) ? 11 - pos : ((pos < 4) ? 12 + ((k & 1) ? 3 - pos : pos) : ((k < 3) ? pos - 4 : 15 - pos));
            if (lt < NPC) {
                sts32(sb + SM_TDEG + (tile * 8 + k) * 4, deg);
                sts8(sb + SM_TNODE + tile * 8 + k, lt);
            }
            asm volatile("bar.sync 5, 96;" ::: "memory");
            if (lt < 16) {
                const uint4 a = lds128(sb + SM_TDEG + lt * 32);
                const uint32_t tot = a.x + a.y + a.z + a.w + lds32(sb + SM_TDEG + lt * 32 + 16);
                if (((tot + 7) & ~7u) > TCAP) sts32(sb + SM_FLAG, 1);
                sts32(sb + SM_TCNT + lt * 4, tot);
            }
        }
        lt_bar();
        TRACE(29);
        if (lds32(sb + SM_FLAG) != 0) {
            if (lt < NPC) sts8(sb + SM_TNODE + (lt & 15) * 8 + (lt >> 4), lt);
        }
        TRACE(30);
    }
    TRACE(31);
    __syncthreads();
    TRACE(32);
    const bool slow = lds32(sb + SM_FLAG) != 0;

    constexpr uint32_t RD = SM_R1 - SM_R0;
    const uint32_t ring0 = sb + SM_R0 + w * STAGE;
    const char* tab_l = p.table + lane * 16;
    asm volatile("" : "+l"(tab_l));
    const char* e_l = (const char*)p.e_attr + (mi & 1) * 16;
    asm volatile("" : "+l"(e_l));
    const uint32_t cpo = lane * 16;
    const uint32_t elo = 4096 + rr * 32 + (((mi & 1) ^ ((rr >> 2) & 1)) << 4);
    const uint32_t lsrc = sb + SM_LSE + w * TCAP * 4, lid = sb + SM_LID + w * TCAP;
    const uint32_t lec = rr * 4;

    auto issue_full = [&](uint32_t lp, uint32_t dl) {
        const uint4 s0 = lds128(lp), s1 = lds128(lp + 16);
        const uint32_t eo = lds32(lp + lec);
        const uint32_t sv[8] = {s0.x, s0.y, s0.z, s0.w, s1.x, s1.y, s1.z, s1.w};
#pragma unroll
        for (int j = 0; j < 8; j++) cp16(ring0 + dl + (cpo ^ (j << 4)) + j * 512, madw(sv[j] & 0x3FFF, 512, tab_l));
        cp16(ring0 + dl + elo, madw(eo >> 14, 32, e_l));
    };
    auto issue0 = [&]() {
        const int cnt = lds32(sb + SM_TCNT + w * 4), nit = (cnt + 7) >> 3;
        if (nit > 0) {
            const int pad = nit * 8 - cnt;
            const uint4 s0 = lds128(lsrc), s1 = lds128(lsrc + 16);
            const uint32_t eo = lds32(lsrc + lec);
            const uint32_t sv[8] = {s0.x, s0.y, s0.z, s0.w, s1.x, s1.y, s1.z, s1.w};
#pragma unroll
            for (int j = 0; j < 8; j++) cp16z(ring0 + (cpo ^ (j << 4)) + j * 512, madw(sv[j] & 0x3FFF, 512, tab_l), (j >= pad) ? 16 : 0);
            cp16z(ring0 + elo, madw(eo >> 14, 32, e_l), (rr >= pad) ? 16 : 0);
        }
        cp_commit();
    };
    auto issue1 = [&]() {
        if ((int)lds32(sb + SM_TCNT + w * 4) > 8) issue_full(lsrc + 32, RD);
        cp_commit();
    };
    uint32_t bar_v = 0;
    if (tid == 0) asm volatile("ld.relaxed.gpu.global.u32 %0, [%1];" : "=r"(bar_v) : "l"(p.bar) : "memory");
    if (!slow) {
        const uint2 tn = lds64(sb + SM_TNODE + w * 8);
        const uint4 dg = lds128(sb + SM_TDEG + w * 32);
        const uint32_t p1 = dg.x, p2 = p1 + dg.y, p3 = p2 + dg.z, p4 = p3 + dg.w, tot = lds32(sb + SM_TCNT + w * 4);
        const uint32_t pad = (0u - tot) & 7u;
        if (lane < pad) { sts8(lid + lane, 0x7F); sts32(lsrc + lane * 4, 0); }
#pragma unroll
        for (int r = 0; r < TCAP / 32; r++) {
            const uint32_t q = lane + 32 * r;
            if (q < tot) {
                const uint32_t sl = (q >= p1) + (q >= p2) + (q >= p3) + (q >= p4);
                const uint32_t pre = (q >= p4) ? p4 : ((q >= p3) ? p3 : ((q >= p2) ? p2 : ((q >= p1) ? p1 : 0)));
                const uint32_t node = prmt(tn.x, tn.y, sl) & 0xFF;
                sts32(lsrc + (pad + q) * 4, lds32(sb + SM_NL + (node * NCAP + q - pre) * 4));
                sts8(lid + pad + q, sl * 16);
            }
        }
    }
    TRACE(10);
    if (tid == 0) {
        int it = 0;
        while ((int)(bar_v - bar_target) < 0 && ++it < (1 << 20))
            asm volatile("ld.relaxed.gpu.global.u32 %0, [%1];" : "=r"(bar_v) : "l"(p.bar) : "memory");
    }
    __syncthreads();
    TRACE(11);
    if (!slow) { issue0(); issue1(); }
    TRACE(33);
    load_node_frags();
    TRACE(34);

    const uint32_t ldo = rr * 512 + ((mi ^ rr) << 4);
    const uint32_t sel = (g | ((8 | g) << 4) | (g << 8) | ((8 | g) << 12)) |
                         (((2 * t) | ((8 | (2 * t)) << 4) | ((2 * t + 1) << 8) | ((8 | (2 * t + 1)) << 12)) << 16);
    const uint32_t gg = (g * 16) | ((g * 16) << 16);
    const uint32_t tt = (t * 32) | ((t * 32 + 16) << 16);

    auto compute = [&](uint32_t st, uint32_t idp) {
        uint32_t eb[2];
        ldsm2(eb, st + elo);
        const uint2 iw = lds64(idp);
        const uint32_t sx = seteq_bf16x2(prmt(iw.x, iw.y, sel), tt);
        const uint32_t sa = seteq_bf16x2(prmt(iw.x, iw.y, sel >> 16), gg);
#pragma unroll
        for (int jj = 0; jj < 4; jj++) {
            uint32_t xb[4], hv[4];
            const uint32_t la = st + (ldo ^ ((jj & 1) << 6)) + (jj >> 1) * 128;
            ldsm4(xb, la);
            ldsm4t(hv, la + 256);
#pragma unroll
            for (int u = 0; u < 2; u++) {
                const int j = 2 * jj + u;
                float d[4];
                mma16816_z(d, Cf[j][0], Cf[j][1], Cf[j][2], Cf[j][3], eb[0], eb[1]);
                mma1688(d, xAf[j][0], xAf[j][1], sx);
                mma16816(d, ident, 0u, 0u, ident, xb[2 * u], xb[2 * u + 1]);
                const uint32_t m0 = fma_bf16x2(pack_bf16(tanh_ap(d[0]), tanh_ap(d[1])), hv[2 * u], hv[2 * u]);
                const uint32_t m1 = fma_bf16x2(pack_bf16(tanh_ap(d[2]), tanh_ap(d[3])), hv[2 * u + 1], hv[2 * u + 1]);
                mma1688(agg[j], m0, m1, sa);
            }
        }
    };

    const int nseg = slow ? NSEG : 1;
#pragma unroll 1
    for (int seg = 0; seg < nseg; seg++) {
        if (slow) {
            __syncthreads();
            if (tid < 16) sts32(sb + SM_TCNT + tid * 4, 0);
            __syncthreads();
            const int e = seg * TCAP + tid;
            int loc = -1; uint32_t r = 0;
            if (tid < TCAP && e < EE) {
                const int dd = __ldg(p.dst + e) - b * NPC;
                if (dd >= 0 && dd < NPC) { loc = dd; r = atoms_add(sb + SM_TCNT + (loc & 15) * 4, 1); }
            }
            __syncthreads();
            if (loc >= 0) {
                const uint32_t tile = loc & 15, tot = lds32(sb + SM_TCNT + tile * 4);
                const uint32_t pos = tile * TCAP + ((0u - tot) & 7u) + r;
                sts32(sb + SM_LSE + pos * 4, (uint32_t)__ldg(p.src + e) | ((uint32_t)e << 14));
                sts8(sb + SM_LID + pos, (loc >> 4) << 4);
            }
            const int pad = (0 - (int)lds32(sb + SM_TCNT + w * 4)) & 7;
            if (lane < pad) { sts8(sb + SM_LID + w * TCAP + lane, 0x7F); sts32(sb + SM_LSE + (w * TCAP + lane) * 4, 0); }
            __syncthreads();
            issue0();
            issue1();
        }
        const int nit = __shfl_sync(0xffffffffu, ((int)lds32(sb + SM_TCNT + w * 4) + 7) >> 3, 0);
        uint32_t st = ring0, so = ring0 + RD, lp = lsrc + 32, idp = lid;
        const uint32_t lend = lsrc + nit * 32;
#pragma unroll 1
        for (; lp <= lend; lp += 32, idp += 8) {
            if (idp == lid) cp_wait<1>(); else cp_wait<0>();
            __syncwarp();
            if (idp != lid && lp < lend) issue_full(lp, so - ring0);
            cp_commit();
            compute(st, idp);
            const uint32_t tmp = st; st = so; so = tmp;
        }
        cp_wait<0>();
        __syncwarp();
    }
    TRACE(35);

    {
        uint32_t o[8][2];
#pragma unroll
        for (int j = 0; j < 8; j++) {
            float v[4];
#pragma unroll
            for (int q = 0; q < 4; q++) { const float h = agg[j][q]; v[q] = fmaf(h, tanh_ap(h), h); }
            o[j][0] = pack_bf16(v[0], v[1]); o[j][1] = pack_bf16(v[2], v[3]);
        }
#pragma unroll
        for (int jp = 0; jp < 4; jp++) {
            const int c = 4 * jp + mi;
            stsm4t(ring0 + rr * 256 + ((c & 8) << 4) + (((c & 7) ^ rr) << 4), o[2 * jp][0], o[2 * jp][1], o[2 * jp + 1][0], o[2 * jp + 1][1]);
        }
        __syncwarp();
#pragma unroll
        for (int i = 0; i < 3; i++) {
            const int idx = lane + 32 * i, row = idx >> 4, c = idx & 15;
            const int nd = b * NPC + (int)lds8(sb + SM_TNODE + w * 8 + (row & 7));
            if (row < nslot && nd < NN) {
                const uint4 v = lds128(ring0 + row * 256 + ((c & 8) << 4) + (((c & 7) ^ row) << 4));
                *(uint4*)((char*)p.out + (size_t)nd * 256 + c * 16) = v;
            }
        }
    }
    TRACE(36);
}

typedef CUresult (*EncodeFn)(CUtensorMap*, CUtensorMapDataType, cuuint32_t, void*, const cuuint64_t*, const cuuint64_t*,
                             const cuuint32_t*, const cuuint32_t*, CUtensorMapInterleave, CUtensorMapSwizzle,
                             CUtensorMapL2promotion, CUtensorMapFloatOOBfill);

static void make_map(EncodeFn enc, CUtensorMap* tm, const void* base, int rows, int cols, int box_rows) {
    cuuint64_t dims[2] = {(cuuint64_t)cols, (cuuint64_t)rows};
    cuuint64_t strides[1] = {(cuuint64_t)cols * 2};
    cuuint32_t box[2] = {64, (cuuint32_t)box_rows};
    cuuint32_t es[2] = {1, 1};
    enc(tm, CU_TENSOR_MAP_DATA_TYPE_BFLOAT16, 2, (void*)base, dims, strides, box, es, CU_TENSOR_MAP_INTERLEAVE_NONE,
        CU_TENSOR_MAP_SWIZZLE_128B, CU_TENSOR_MAP_L2_PROMOTION_NONE, CU_TENSOR_MAP_FLOAT_OOB_FILL_NONE);
}

}

extern "C" void kernel_launch(void* const* d_in, const int* in_sizes, int n_in, void* d_out, int out_size) {
    using namespace egc;
    (void)in_sizes; (void)n_in; (void)out_size;
    static EncodeFn enc = nullptr;
    static void* table = nullptr;
    static void* xch = nullptr;
    static void* bar = nullptr;
    if (!enc) {
        void* fn = nullptr;
        cudaDriverEntryPointQueryResult qr;
        cudaGetDriverEntryPoint("cuTensorMapEncodeTiled", &fn, cudaEnableDefault, &qr);
        enc = (EncodeFn)fn;
        cudaGetSymbolAddress(&table, g_table);
        cudaGetSymbolAddress(&xch, g_xch);
        cudaGetSymbolAddress(&bar, g_bar);
        cudaFuncSetAttribute(egc_kernel, cudaFuncAttributeMaxDynamicSharedMemorySize, SMEM_BYTES);
    }
    CUtensorMap tm_x, tm_g, tm_u, tm_v, tm_t;
    make_map(enc, &tm_x, d_in[0], NN, 128, 80);
    make_map(enc, &tm_u, d_in[4], 128, 128, 128);
    make_map(enc, &tm_v, d_in[5], 128, 128, 128);
    make_map(enc, &tm_g, d_in[6], 272, 128, 128);
    make_map(enc, &tm_t, table, NN, 256, NPC);
    Params p;
    p.e_attr = (const bf16*)d_in[1];
    p.src = (const int*)d_in[2];
    p.dst = (const int*)d_in[3];
    p.gw = (const bf16*)d_in[6];
    p.out = (bf16*)d_out;
    p.bar = (unsigned*)bar;
    p.xch = (uint4*)xch;
    p.table = (const char*)table;
    egc_kernel<<<NCTA, NTHR, SMEM_BYTES, cudaStreamPerThread>>>(p, tm_x, tm_g, tm_u, tm_v, tm_t);
}
```

```cpp
#include <cuda_runtime.h>
#include <cuda_bf16.h>
#include <cuda.h>
#include <stdint.h>
#include <type_traits>

namespace egc {

typedef __nv_bfloat16 bf16;

constexpr int NN = 10000, EE = 160000;
constexpr int NCTA = 132, NPC = 76, ECH = 1216, NTHR = 512;
constexpr int PIECES = 10, XCAP = 3 * PIECES;
constexpr int TCAP = 96;
constexpr int NSEG = (EE + TCAP - 1) / TCAP;
constexpr int SPIN_LIMIT = 1 << 20;
constexpr uint32_t START_DELAY = 550;

constexpr int STAGE = 4352;
constexpr int SM_R0 = 0;
constexpr int SM_R1 = 16 * STAGE;
constexpr int SM_S = SM_R1;
constexpr int SM_WU = SM_R1 + 8 * STAGE;
constexpr int SM_WA = SM_R1 + 16 * STAGE;
constexpr int SM_X = SM_WA + 32768;
constexpr int SM_C = SM_X + 20480;
constexpr int SM_LSE = SM_C + 4096;
constexpr int SM_LID = SM_LSE + 6144 + 128;
constexpr int SM_HIST = SM_LID + 1536 + 32;
constexpr int SM_KEYS = SM_HIST + 544;
constexpr int SM_CURS = SM_KEYS + 512;
constexpr int SM_DBIN = SM_CURS + 512;
constexpr int SM_TDEG = SM_DBIN + 256;
constexpr int SM_TNODE = SM_TDEG + 512;
constexpr int SM_TCNT = SM_TNODE + 128;
constexpr int SM_FLAG = SM_TCNT + 64;
constexpr int NCAP = 40;
constexpr int SM_NL = SM_FLAG + 16;
constexpr int SM_BAR = SM_NL + NPC * NCAP * 4 + 128;
constexpr int SM_TRACE = SM_BAR + 9 * 8 + 8;
constexpr int SM_END = SM_TRACE + 2 * 48 * 4;
constexpr int SMEM_BYTES = SM_END + 1024;

__device__ __align__(1024) uint4 g_table[NN * 32];
__device__ __align__(1024) uint4 g_xch[NCTA * NCTA * PIECES];
__device__ __align__(128) unsigned g_bar[32];
#define TRACE(i) do {} while (0)

__device__ __forceinline__ void mma16816(float* d, uint32_t a0, uint32_t a1, uint32_t a2, uint32_t a3, uint32_t b0, uint32_t b1) {
    asm("mma.sync.aligned.m16n8k16.row.col.f32.bf16.bf16.f32 {%0,%1,%2,%3}, {%4,%5,%6,%7}, {%8,%9}, {%0,%1,%2,%3};"
        : "+f"(d[0]), "+f"(d[1]), "+f"(d[2]), "+f"(d[3]) : "r"(a0), "r"(a1), "r"(a2), "r"(a3), "r"(b0), "r"(b1));
}
__device__ __forceinline__ void mma16816_z(float* d, uint32_t a0, uint32_t a1, uint32_t a2, uint32_t a3, uint32_t b0, uint32_t b1) {
    asm("mma.sync.aligned.m16n8k16.row.col.f32.bf16.bf16.f32 {%0,%1,%2,%3}, {%4,%5,%6,%7}, {%8,%9}, {%10,%10,%10,%10};"
        : "=f"(d[0]), "=f"(d[1]), "=f"(d[2]), "=f"(d[3]) : "r"(a0), "r"(a1), "r"(a2), "r"(a3), "r"(b0), "r"(b1), "f"(0.f));
}
__device__ __forceinline__ void mma1688(float* d, uint32_t a0, uint32_t a1, uint32_t b0) {
    asm("mma.sync.aligned.m16n8k8.row.col.f32.bf16.bf16.f32 {%0,%1,%2,%3}, {%4,%5}, {%6}, {%0,%1,%2,%3};"
        : "+f"(d[0]), "+f"(d[1]), "+f"(d[2]), "+f"(d[3]) : "r"(a0), "r"(a1), "r"(b0));
}
__device__ __forceinline__ void mma1688_z(float* d, uint32_t a0, uint32_t a1, uint32_t b0) {
    asm("mma.sync.aligned.m16n8k8.row.col.f32.bf16.bf16.f32 {%0,%1,%2,%3}, {%4,%5}, {%6}, {%7,%7,%7,%7};"
        : "=f"(d[0]), "=f"(d[1]), "=f"(d[2]), "=f"(d[3]) : "r"(a0), "r"(a1), "r"(b0), "f"(0.f));
}
__device__ __forceinline__ void ldsm4(uint32_t* r, uint32_t addr) {
    asm volatile("ldmatrix.sync.aligned.m8n8.x4.shared.b16 {%0,%1,%2,%3}, [%4];" : "=r"(r[0]), "=r"(r[1]), "=r"(r[2]), "=r"(r[3]) : "r"(addr) : "memory");
}
__device__ __forceinline__ void ldsm4t(uint32_t* r, uint32_t addr) {
    asm volatile("ldmatrix.sync.aligned.m8n8.x4.trans.shared.b16 {%0,%1,%2,%3}, [%4];" : "=r"(r[0]), "=r"(r[1]), "=r"(r[2]), "=r"(r[3]) : "r"(addr) : "memory");
}
__device__ __forceinline__ void ldsm2(uint32_t* r, uint32_t addr) {
    asm volatile("ldmatrix.sync.aligned.m8n8.x2.shared.b16 {%0,%1}, [%2];" : "=r"(r[0]), "=r"(r[1]) : "r"(addr) : "memory");
}
__device__ __forceinline__ void stsm4t(uint32_t addr, uint32_t r0, uint32_t r1, uint32_t r2, uint32_t r3) {
    asm volatile("stmatrix.sync.aligned.m8n8.x4.trans.shared.b16 [%0], {%1,%2,%3,%4};" :: "r"(addr), "r"(r0), "r"(r1), "r"(r2), "r"(r3) : "memory");
}
__device__ __forceinline__ float tanh_ap(float x) { float r; asm("tanh.approx.f32 %0, %1;" : "=f"(r) : "f"(x)); return r; }
__device__ __forceinline__ uint32_t pack_bf16(float lo, float hi) { uint32_t r; asm("cvt.rn.bf16x2.f32 %0, %1, %2;" : "=r"(r) : "f"(hi), "f"(lo)); return r; }
__device__ __forceinline__ uint32_t fma_bf16x2(uint32_t a, uint32_t b, uint32_t c) { uint32_t r; asm("fma.rn.bf16x2 %0, %1, %2, %3;" : "=r"(r) : "r"(a), "r"(b), "r"(c)); return r; }
__device__ __forceinline__ uint32_t mul_bf16x2(uint32_t a, uint32_t b) { uint32_t r; asm("mul.rn.bf16x2 %0, %1, %2;" : "=r"(r) : "r"(a), "r"(b)); return r; }
__device__ __forceinline__ uint32_t seteq_bf16x2(uint32_t a, uint32_t b) { uint32_t r; asm("set.eq.bf16x2.bf16x2 %0, %1, %2;" : "=r"(r) : "r"(a), "r"(b)); return r; }
__device__ __forceinline__ uint32_t prmt(uint32_t a, uint32_t b, uint32_t s) { uint32_t r; asm("prmt.b32 %0, %1, %2, %3;" : "=r"(r) : "r"(a), "r"(b), "r"(s)); return r; }
__device__ __forceinline__ uint32_t shl_clamp(uint32_t a, uint32_t s) { uint32_t r; asm("shl.b32 %0, %1, %2;" : "=r"(r) : "r"(a), "r"(s)); return r; }
__device__ __forceinline__ void cp16(uint32_t dst, const void* src) { asm volatile("cp.async.cg.shared.global [%0], [%1], 16;" :: "r"(dst), "l"(src) : "memory"); }
__device__ __forceinline__ void cp16z(uint32_t dst, const void* src, uint32_t sz) { asm volatile("cp.async.cg.shared.global [%0], [%1], 16, %2;" :: "r"(dst), "l"(src), "r"(sz) : "memory"); }
__device__ __forceinline__ const void* madw(uint32_t a, uint32_t m, const void* base) {
    const void* r; asm("mad.wide.u32 %0, %1, %2, %3;" : "=l"(r) : "r"(a), "r"(m), "l"(base)); return r;
}
__device__ __forceinline__ void cp16_p(bool p, uint32_t dst, const void* src) {
    asm volatile("{\n.reg .pred p;\nsetp.ne.u32 p, %2, 0;\n@p cp.async.cg.shared.global [%0], [%1], 16;\n}" :: "r"(dst), "l"(src), "r"((uint32_t)p) : "memory");
}
__device__ __forceinline__ void cp_commit() { asm volatile("cp.async.commit_group;" ::: "memory"); }
template <int N> __device__ __forceinline__ void cp_wait() { asm volatile("cp.async.wait_group %0;" :: "n"(N) : "memory"); }
__device__ __forceinline__ uint4 lds128(uint32_t a) { uint4 v; asm volatile("ld.shared.v4.u32 {%0,%1,%2,%3}, [%4];" : "=r"(v.x), "=r"(v.y), "=r"(v.z), "=r"(v.w) : "r"(a) : "memory"); return v; }
__device__ __forceinline__ uint2 lds64(uint32_t a) { uint2 v; asm volatile("ld.shared.v2.u32 {%0,%1}, [%2];" : "=r"(v.x), "=r"(v.y) : "r"(a) : "memory"); return v; }
__device__ __forceinline__ uint32_t lds32(uint32_t a) { uint32_t v; asm volatile("ld.shared.u32 %0, [%1];" : "=r"(v) : "r"(a) : "memory"); return v; }
__device__ __forceinline__ uint32_t lds8(uint32_t a) { uint32_t v; asm volatile("ld.shared.u8 %0, [%1];" : "=r"(v) : "r"(a) : "memory"); return v; }
__device__ __forceinline__ void sts32(uint32_t a, uint32_t v) { asm volatile("st.shared.u32 [%0], %1;" :: "r"(a), "r"(v) : "memory"); }
__device__ __forceinline__ void sts8(uint32_t a, uint32_t v) { asm volatile("st.shared.u8 [%0], %1;" :: "r"(a), "r"(v) : "memory"); }
__device__ __forceinline__ void sts128(uint32_t a, uint4 v) { asm volatile("st.shared.v4.u32 [%0], {%1,%2,%3,%4};" :: "r"(a), "r"(v.x), "r"(v.y), "r"(v.z), "r"(v.w) : "memory"); }
__device__ __forceinline__ uint32_t atoms_add(uint32_t a, uint32_t v) { uint32_t r; asm volatile("atom.shared.add.u32 %0, [%1], %2;" : "=r"(r) : "r"(a), "r"(v) : "memory"); return r; }
__device__ __forceinline__ void reds_add(uint32_t a, uint32_t v) { asm volatile("red.shared.add.u32 [%0], %1;" :: "r"(a), "r"(v) : "memory"); }
__device__ __forceinline__ uint32_t atoms_add_p(bool p, uint32_t a, uint32_t v) {
    uint32_t r = 0;
    asm volatile("{\n.reg .pred p;\nsetp.ne.u32 p, %3, 0;\n@p atom.shared.add.u32 %0, [%1], %2;\n}" : "+r"(r) : "r"(a), "r"(v), "r"((uint32_t)p) : "memory");
    return r;
}
__device__ __forceinline__ uint32_t lds32_p(bool p, uint32_t a) {
    uint32_t r = 0;
    asm volatile("{\n.reg .pred p;\nsetp.ne.u32 p, %2, 0;\n@p ld.shared.u32 %0, [%1];\n}" : "+r"(r) : "r"(a), "r"((uint32_t)p) : "memory");
    return r;
}
__device__ __forceinline__ void sts32_p(bool p, uint32_t a, uint32_t v) {
    asm volatile("{\n.reg .pred p;\nsetp.ne.u32 p, %2, 0;\n@p st.shared.u32 [%0], %1;\n}" :: "r"(a), "r"(v), "r"((uint32_t)p) : "memory");
}
__device__ __forceinline__ void sts8_p(bool p, uint32_t a, uint32_t v) {
    asm volatile("{\n.reg .pred p;\nsetp.ne.u32 p, %2, 0;\n@p st.shared.u8 [%0], %1;\n}" :: "r"(a), "r"(v), "r"((uint32_t)p) : "memory");
}
__device__ __forceinline__ void st_piece(uint4* p, uint4 v) {
    asm volatile("{\n.reg .b128 q;\n.reg .b64 lo, hi;\nmov.b64 lo, {%1,%2};\nmov.b64 hi, {%3,%4};\nmov.b128 q, {lo, hi};\nst.relaxed.gpu.global.b128 [%0], q;\n}"
                 :: "l"(p), "r"(v.x), "r"(v.y), "r"(v.z), "r"(v.w) : "memory");
}
__device__ __forceinline__ uint4 ld_piece(const uint4* p) {
    uint4 v;
    asm volatile("{\n.reg .b128 q;\n.reg .b64 lo, hi;\nld.relaxed.gpu.global.b128 q, [%4];\nmov.b128 {lo, hi}, q;\nmov.b64 {%0,%1}, lo;\nmov.b64 {%2,%3}, hi;\n}"
                 : "=r"(v.x), "=r"(v.y), "=r"(v.z), "=r"(v.w) : "l"(p) : "memory");
    return v;
}
__device__ __forceinline__ void mbar_init(uint32_t bar, uint32_t cnt) { asm volatile("mbarrier.init.shared::cta.b64 [%0], %1;" :: "r"(bar), "r"(cnt) : "memory"); }
__device__ __forceinline__ void mbar_expect(uint32_t bar, uint32_t bytes) { asm volatile("mbarrier.arrive.expect_tx.shared::cta.b64 _, [%0], %1;" :: "r"(bar), "r"(bytes) : "memory"); }
__device__ __forceinline__ void mbar_wait(uint32_t bar, uint32_t parity) {
    uint32_t ok; int it = 0;
    do {
        asm volatile("{\n.reg .pred p;\nmbarrier.try_wait.parity.shared::cta.b64 p, [%1], %2;\nselp.u32 %0, 1, 0, p;\n}" : "=r"(ok) : "r"(bar), "r"(parity) : "memory");
    } while (!ok && ++it < (1 << 22));
}
__device__ __forceinline__ void tma_load2d(uint32_t dst, const CUtensorMap* tm, int c0, int c1, uint32_t bar) {
    asm volatile("cp.async.bulk.tensor.2d.shared::cluster.global.mbarrier::complete_tx::bytes [%0], [%1, {%3, %4}], [%2];"
                 :: "r"(dst), "l"(tm), "r"(bar), "r"(c0), "r"(c1) : "memory");
}
__device__ __forceinline__ void tma_load2d_mc(uint32_t dst, const CUtensorMap* tm, int c0, int c1, uint32_t bar) {
    asm volatile("cp.async.bulk.tensor.2d.shared::cluster.global.mbarrier::complete_tx::bytes.multicast::cluster [%0], [%1, {%3, %4}], [%2], %5;"
                 :: "r"(dst), "l"(tm), "r"(bar), "r"(c0), "r"(c1), "h"((uint16_t)3) : "memory");
}
__device__ __forceinline__ void tma_store2d(const CUtensorMap* tm, int c0, int c1, uint32_t src) {
    asm volatile("cp.async.bulk.tensor.2d.global.shared::cta.bulk_group [%0, {%2, %3}], [%1];"
                 :: "l"(tm), "r"(src), "r"(c0), "r"(c1) : "memory");
}
__device__ __forceinline__ void spin(uint32_t cycles) {
    uint32_t c0, c1;
    asm volatile("mov.u32 %0, %%clock;" : "=r"(c0));
    do { asm volatile("mov.u32 %0, %%clock;" : "=r"(c1)); } while (c1 - c0 < cycles);
}
__device__ __forceinline__ void lt_bar() { asm volatile("bar.sync 3, 256;" ::: "memory"); }
__device__ __forceinline__ void wg_bar(int id) { asm volatile("bar.sync %0, 128;" :: "r"(id) : "memory"); }

__device__ __forceinline__ void wgmma_n80(float (&d)[40], uint64_t da, uint64_t db, int acc) {
    asm volatile("{\n.reg .pred p;\nsetp.ne.b32 p, %42, 0;\n"
        "wgmma.mma_async.sync.aligned.m64n80k16.f32.bf16.bf16 "
        "{%0,%1,%2,%3,%4,%5,%6,%7,%8,%9,%10,%11,%12,%13,%14,%15,%16,%17,%18,%19,"
        "%20,%21,%22,%23,%24,%25,%26,%27,%28,%29,%30,%31,%32,%33,%34,%35,%36,%37,%38,%39}, "
        "%40, %41, p, 1, 1, 1, 0;\n}\n"
        : "+f"(d[0]), "+f"(d[1]), "+f"(d[2]), "+f"(d[3]), "+f"(d[4]), "+f"(d[5]), "+f"(d[6]), "+f"(d[7]), "+f"(d[8]), "+f"(d[9]),
          "+f"(d[10]), "+f"(d[11]), "+f"(d[12]), "+f"(d[13]), "+f"(d[14]), "+f"(d[15]), "+f"(d[16]), "+f"(d[17]), "+f"(d[18]), "+f"(d[19]),
          "+f"(d[20]), "+f"(d[21]), "+f"(d[22]), "+f"(d[23]), "+f"(d[24]), "+f"(d[25]), "+f"(d[26]), "+f"(d[27]), "+f"(d[28]), "+f"(d[29]),
          "+f"(d[30]), "+f"(d[31]), "+f"(d[32]), "+f"(d[33]), "+f"(d[34]), "+f"(d[35]), "+f"(d[36]), "+f"(d[37]), "+f"(d[38]), "+f"(d[39])
        : "l"(da), "l"(db), "r"(acc));
}

__device__ __forceinline__ void gemm_issue(float (&d)[40], uint32_t wbase, uint32_t xbase) {
    asm volatile("wgmma.fence.sync.aligned;" ::: "memory");
#pragma unroll
    for (int s = 0; s < 8; s++) {
        const uint32_t aa = wbase + s * 2048, ab = xbase + (s >> 2) * 10240 + (s & 3) * 32;
        const uint64_t da = (uint64_t)((aa & 0x3FFFF) >> 4) | ((uint64_t)64 << 16) | ((uint64_t)64 << 32) | ((uint64_t)1 << 62);
        const uint64_t db = (uint64_t)((ab & 0x3FFFF) >> 4) | ((uint64_t)1 << 16) | ((uint64_t)64 << 32) | ((uint64_t)1 << 62);
        wgmma_n80(d, da, db, s > 0);
    }
    asm volatile("wgmma.commit_group.sync.aligned;" ::: "memory");
}
__device__ __forceinline__ void gemm_wait(float (&d)[40]) {
    asm volatile("wgmma.wait_group.sync.aligned 0;" ::: "memory");
#pragma unroll
    for (int i = 0; i < 40; i++) asm volatile("" : "+f"(d[i]) :: "memory");
}
__device__ __forceinline__ void gemm_store(const float (&d)[40], float sc, uint32_t base, int w4, int lane) {
    const int mi = lane >> 3, rr = lane & 7;
    const uint32_t sa = base + (rr + 8 * (mi >> 1)) * 128 + (((2 * w4 + (mi & 1)) ^ rr) << 4);
#pragma unroll
    for (int p = 0; p < 5; p++) {
        const float* q = d + 8 * p;
        stsm4t(sa + p * 2048, pack_bf16(q[0] * sc, q[1] * sc), pack_bf16(q[2] * sc, q[3] * sc),
               pack_bf16(q[4] * sc, q[5] * sc), pack_bf16(q[6] * sc, q[7] * sc));
    }
}

struct Params {
    const int* dst;
    const int* src;
    unsigned* bar;
    uint4* xch;
    const bf16* gw;
    const bf16* e_attr;
    const char* table;
    bf16* out;
};

__global__ void __launch_bounds__(NTHR, 1)
egc_kernel(const Params p, const __grid_constant__ CUtensorMap tm_x, const __grid_constant__ CUtensorMap tm_g,
           const __grid_constant__ CUtensorMap tm_u, const __grid_constant__ CUtensorMap tm_v, const __grid_constant__ CUtensorMap tm_t) {
    extern __shared__ unsigned char smem_raw[];
    const uint32_t sb = ((uint32_t)__cvta_generic_to_shared(smem_raw) + 1023u) & ~1023u;
    const int tid = threadIdx.x, lane = tid & 31, b = blockIdx.x;
    const int w = __shfl_sync(0xffffffffu, tid >> 5, 0);
    const int wq = w >> 2, w4 = w & 3;
    const int g = lane >> 2, t = lane & 3, mi = lane >> 3, rr = lane & 7;
    TRACE(0);

    uint32_t Cf[8][4];
    auto load_cf = [&]() {
        const int krow = rr + 8 * (mi >> 1);
#pragma unroll
        for (int j = 0; j < 8; j++) {
            const int c = 2 * j + (mi & 1);
            ldsm4t(Cf[j], sb + SM_C + krow * 256 + ((c & 8) << 4) + (((c & 7) ^ rr) << 4));
#pragma unroll
            for (int q = 0; q < 4; q++) Cf[j][q] = mul_bf16x2(Cf[j][q], 0x3F003F00u);
        }
    };
    uint32_t xAf[8][2];
    float agg[8][4];
    const uint32_t ident = (g == 2 * t) ? 0x3F80u : ((g == 2 * t + 1) ? 0x3F800000u : 0u);
    const int nslot = (w < 12) ? 5 : 4;
    auto load_node_frags = [&]() {
        const int mynode = lds8(sb + SM_TNODE + w * 8 + ((rr < nslot) ? rr : 0));
#pragma unroll
        for (int jp = 0; jp < 4; jp++) {
            const int c = 4 * jp + mi;
            const uint32_t off = mynode * 128 + (((c & 7) ^ (mynode & 7)) << 4);
            uint32_t q[4];
            ldsm4t(q, sb + SM_WA + (c >> 3) * 16384 + off);
            xAf[2 * jp][0] = q[0]; xAf[2 * jp][1] = q[1]; xAf[2 * jp + 1][0] = q[2]; xAf[2 * jp + 1][1] = q[3];
            ldsm4t(q, sb + SM_X + (c >> 3) * 10240 + off);
            mma1688_z(agg[2 * jp], q[0], q[1], ident);
            mma1688_z(agg[2 * jp + 1], q[2], q[3], ident);
        }
    };
    uint32_t bar_target = 0;
    constexpr int LT = 256;
    if (wq < 2) {
        uint32_t epoch = 0;
        {
            const int r = tid >> 4, c = tid & 15;
            cp16(sb + SM_C + r * 256 + ((c & 8) << 4) + (((c & 7) ^ (r & 7)) << 4), p.gw + (256 + r) * 128 + c * 8);
            cp_commit();
        }
        if (tid == 0) {
            asm volatile("ld.relaxed.gpu.global.u32 %0, [%1];" : "=r"(epoch) : "l"(p.bar) : "memory");
            for (int i = 0; i < 9; i++) mbar_init(sb + SM_BAR + i * 8, 1);
            asm volatile("fence.mbarrier_init.release.cluster;" ::: "memory");
            const uint32_t bx = sb + SM_BAR;
            mbar_expect(bx, 20480);
#pragma unroll
            for (int i = 0; i < 8; i++) mbar_expect(bx + 8 + i * 8, 16384);
            spin(START_DELAY);
            tma_load2d(sb + SM_X, &tm_x, 0, b * NPC, bx);
            tma_load2d(sb + SM_X + 10240, &tm_x, 64, b * NPC, bx);
            tma_load2d(sb + SM_R0, &tm_g, 0, 128, bx + 8);
            tma_load2d(sb + SM_R0 + 16384, &tm_g, 64, 128, bx + 16);
            tma_load2d(sb + SM_R0 + 2 * 16384, &tm_v, 0, 0, bx + 24);
            tma_load2d(sb + SM_R0 + 3 * 16384, &tm_v, 64, 0, bx + 32);
        }
        cp_wait<0>();
        asm volatile("bar.sync 6, 256;" ::: "memory");
        asm volatile("bar.arrive 8, 512;" ::: "memory");
        TRACE(1);
        load_cf();
        float d[40];
        const uint32_t xt = sb + SM_X;
        const bool elect = (w4 == 0 && lane == 0);
        mbar_wait(sb + SM_BAR, 0);
#pragma unroll 1
        for (int r = 0; r < 4; r++) {
            const uint32_t wt = sb + ((r < 2) ? SM_R0 + r * 32768 : ((r == 2) ? SM_WA : SM_WU)) + wq * 16384;
            mbar_wait(sb + SM_BAR + 8 + (2 * r + wq) * 8, 0);
            TRACE(2 + 2 * r);
            gemm_issue(d, wt, xt);
            if (r == 0 && tid == 0) {
#pragma unroll
                for (int i = 0; i < 2; i++) {
                    tma_load2d(sb + SM_WA + i * 16384, &tm_g, i * 64, 0, sb + SM_BAR + 8 + (4 + i) * 8);
                    tma_load2d(sb + SM_WU + i * 16384, &tm_u, i * 64, 0, sb + SM_BAR + 8 + (6 + i) * 8);
                }
            }
            if (r == 2) {
                asm volatile("bar.sync 4, 512;" ::: "memory");
                if (elect) {
                    asm volatile("cp.async.bulk.wait_group 0;" ::: "memory");
                    asm volatile("fence.proxy.async.global;" ::: "memory");
                    asm volatile("red.relaxed.gpu.global.add.u32 [%0], 1;" :: "l"(p.bar) : "memory");
                }
            }
            if (r == 3 && tid == 0) {
                const int e0 = b * ECH, ne = min(ECH, EE - e0);
                asm volatile("cp.async.bulk.prefetch.L2.global [%0], %1;" :: "l"(p.e_attr + (size_t)e0 * 16), "r"(ne * 32) : "memory");
            }
            __syncwarp();
            gemm_wait(d);
            if (r < 3) wg_bar(1 + wq); else asm volatile("bar.sync 6, 256;" ::: "memory");
            gemm_store(d, (r == 1) ? 0.25f : 0.5f, (r < 3) ? wt : xt + wq * 10240, w4, lane);
            if (r < 2) {
                asm volatile("fence.proxy.async.shared::cta;" ::: "memory");
                wg_bar(1 + wq);
                if (elect) {
                    tma_store2d(&tm_t, (2 * r + wq) * 64, b * NPC, wt);
                    asm volatile("cp.async.bulk.commit_group;" ::: "memory");
                }
                __syncwarp();
            }
            TRACE(3 + 2 * r);
        }

        bar_target = (epoch / (2 * NCTA) + 1) * (2 * NCTA);
        TRACE(9);
    } else {
        const int lt = tid - LT;
        int ed[5], es[5];
        uint32_t epoch;
#pragma unroll
        for (int m = 0; m < 5; m++) {
            const int k = lt + m * LT, e = b * ECH + k;
            ed[m] = ((k < ECH) && (e < EE)) ? __ldg(p.dst + e) : -1;
        }
#pragma unroll
        for (int m = 0; m < 5; m++) {
            const int k = lt + m * LT, e = b * ECH + k;
            es[m] = ((k < ECH) && (e < EE)) ? __ldg(p.src + e) : 0;
        }
        asm volatile("ld.relaxed.gpu.global.u32 %0, [%1];" : "=r"(epoch) : "l"(p.bar) : "memory");
        if (lt < 136) sts32(sb + SM_HIST + lt * 4, 0);
        if (lt < 128) { sts32(sb + SM_KEYS + lt * 4, 0); sts32(sb + SM_TDEG + lt * 4, 0); }
        if (lt < 64) sts32(sb + SM_DBIN + lt * 4, 0);
        if (lt == 0) sts32(sb + SM_FLAG, 0);
        lt_bar();
        TRACE(24);
        {
            uint32_t jj[5], rk[5];
#pragma unroll
            for (int m = 0; m < 5; m++) {
                jj[m] = (ed[m] >= 0) ? (((uint32_t)ed[m] * 55189u) >> 22) : (132 + (lane & 3));
                rk[m] = atoms_add(sb + SM_HIST + jj[m] * 4, 1);
            }
#pragma unroll
            for (int m = 0; m < 5; m++) {
                const uint32_t loc = (uint32_t)ed[m] - jj[m] * NPC;
                const uint32_t q = (rk[m] * 43691u) >> 17;
                const uint32_t off = jj[m] * (PIECES * 16) + q * 16 + (rk[m] - 3 * q + 1) * 4;
                sts32(sb + SM_S + ((ed[m] >= 0 && rk[m] < XCAP) ? off : NCTA * PIECES * 16 + lane * 4),
                      (uint32_t)es[m] | (loc << 14) | ((uint32_t)(lt + m * LT) << 21));
            }
        }
        const uint32_t bar_q = epoch / (2 * NCTA);
        epoch = (bar_q + 1) & 0xFFFFFF;
        TRACE(25);
        lt_bar();
        {
            uint4 v[6]; uint32_t c[6];
#pragma unroll
            for (int m = 0; m < 6; m++) {
                const int pc = min(lt + m * LT, NCTA * PIECES - 1);
                v[m] = lds128(sb + SM_S + pc * 16);
                c[m] = lds32(sb + SM_HIST + ((pc * 6554) >> 16) * 4);
            }
#pragma unroll
            for (int m = 0; m < 6; m++) {
                const int pc = lt + m * LT;
                const int j = (pc * 6554) >> 16, q = pc - j * PIECES;
                if ((m < 5 || pc < NCTA * PIECES) && (q < 4 || c[m] > 3 * (q & ~1) || b >= 128)) {
                    v[m].x = (epoch << 8) | min(c[m], 255u);
                    st_piece(p.xch + (((j * (PIECES / 2) + (q >> 1)) * NCTA + b) * 2 + (q & 1)), v[m]);
                }
            }
        }
        TRACE(46);
        asm volatile("bar.arrive 4, 512;" ::: "memory");
        lt_bar();
        if (lt == 0) asm volatile("red.relaxed.gpu.global.add.u32 [%0], 1;" :: "l"(p.bar + 1) : "memory");
        asm volatile("bar.sync 8, 512;" ::: "memory");
        load_cf();
        if (lt == 0) {
            uint32_t v; int it = 0;
            const uint32_t target = bar_q * NCTA + NCTA / 2;
            do { asm volatile("ld.relaxed.gpu.global.u32 %0, [%1];" : "=r"(v) : "l"(p.bar + 1) : "memory"); }
            while ((int)(v - target) < 0 && ++it < SPIN_LIMIT);
        }
        lt_bar();
        TRACE(26);
        uint4 pv[6];
        const int pi5 = 128 + ((lt >> 1) & 3), pq5 = 2 * (lt >> 3) + (lt & 1);
        const uint4* px0 = p.xch + b * (NCTA * PIECES) + lt;
        const uint4* px5 = p.xch + b * (NCTA * PIECES) + (lt >> 3) * (2 * NCTA) + 256 + (lt & 7);
        const uint32_t tg = epoch << 8;
        auto fetch = [&](const uint4* a) {
            uint4 v = ld_piece(a);
            int it = 0;
            while (((v.x ^ tg) >> 8) && ++it < SPIN_LIMIT) { __nanosleep(100); v = ld_piece(a); }
            return v;
        };
        pv[0] = ld_piece(px0);
        pv[1] = ld_piece(px0 + 2 * NCTA);
        pv[5] = (lt < 4 * PIECES) ? ld_piece(px5) : make_uint4(tg, 0, 0, 0);
        for (int it = 0; (((pv[0].x ^ tg) | (pv[1].x ^ tg) | (pv[5].x ^ tg)) >> 8) && it < SPIN_LIMIT; it++) {
            __nanosleep(100);
            if ((pv[0].x ^ tg) >> 8) pv[0] = ld_piece(px0);
            if ((pv[1].x ^ tg) >> 8) pv[1] = ld_piece(px0 + 2 * NCTA);
            if ((pv[5].x ^ tg) >> 8) pv[5] = ld_piece(px5);
        }
        const int cnt = pv[0].x & 255, cnt5 = pv[5].x & 255;
#pragma unroll
        for (int m = 2; m < 5; m++) pv[m] = (cnt > 6 * m) ? ld_piece(px0 + m * (2 * NCTA)) : make_uint4(tg, 0, 0, 0);
        if (cnt > XCAP || cnt5 > XCAP) sts32(sb + SM_FLAG, 1);
        TRACE(27);
        const uint32_t dmy = (96 + lane) * 4;
        uint32_t ao[9], rk[9];
        auto count = [&](int m, int o) {
            const int nv = (m < 5) ? cnt - 3 * (2 * m + (lt & 1)) : cnt5 - 3 * pq5;
#pragma unroll
            for (int s = 0; s < 3; s++) {
                const uint32_t pl = (s == 0) ? pv[m].y : ((s == 1) ? pv[m].z : pv[m].w);
                ao[o + s] = (nv > s) ? ((pl >> 12) & 0x1FC) : dmy;
                rk[o + s] = atoms_add(sb + SM_KEYS + ao[o + s], 1);
            }
        };
        auto put = [&](int m, int o) {
            const uint32_t e0s = (uint32_t)(((m < 5) ? (lt >> 1) : pi5) * ECH) << 14;
#pragma unroll
            for (int s = 0; s < 3; s++) {
                const uint32_t pl = (s == 0) ? pv[m].y : ((s == 1) ? pv[m].z : pv[m].w);
                const bool ok = ao[o + s] < 96 * 4 && rk[o + s] < NCAP;
                sts32(sb + SM_NL + (ok ? ao[o + s] * NCAP + rk[o + s] * 4 : NPC * NCAP * 4 + lane * 4), (pl & 0x3FFF) + ((pl >> 21) << 14) + e0s);
            }
        };
        count(0, 0);
        count(1, 3);
        const bool has5 = lt < 64;
        if (has5) count(5, 6);
        put(0, 0);
        put(1, 3);
        if (has5) put(5, 6);
        if (((pv[2].x ^ tg) | (pv[3].x ^ tg) | (pv[4].x ^ tg)) >> 8) {
#pragma unroll
            for (int m = 2; m < 5; m++) if (cnt > 6 * m) pv[m] = fetch(px0 + m * (2 * NCTA));
        }
#pragma unroll
        for (int m = 2; m < 5; m++) {
            if (__any_sync(0xffffffffu, cnt > 6 * m)) { count(m, 0); put(m, 0); }
        }
        TRACE(28);
        lt_bar();
        if (lt < 96) {
            const uint32_t deg = (lt < NPC) ? lds32(sb + SM_KEYS + lt * 4) : 0;
            const uint32_t bin = 63 - min(deg, 63u);
            const uint32_t r0 = atoms_add_p(lt < NPC, sb + SM_DBIN + bin * 4, 1);
            if (deg > NCAP) sts32(sb + SM_FLAG, 1);
            asm volatile("bar.sync 5, 96;" ::: "memory");
            const uint2 c2 = lds64(sb + SM_DBIN + lane * 8);
            uint32_t inc = c2.x + c2.y;
#pragma unroll
            for (int o = 1; o < 32; o <<= 1) { const uint32_t u = __shfl_up_sync(0xffffffffu, inc, o); if (lane >= o) inc += u; }
            const uint32_t ex = inc - c2.x - c2.y;
            const uint32_t pe = __shfl_sync(0xffffffffu, ex, bin >> 1), p0 = __shfl_sync(0xffffffffu, c2.x, bin >> 1);
            const int rank = pe + ((bin & 1) ? p0 : 0) + r0;
            const int k = rank >> 4, pos = rank & 15;
            const int tile = (k == 4) ? 11 - pos : ((pos < 4) ? 12 + ((k & 1) ? 3 - pos : pos) : ((k < 3) ? pos - 4 : 15 - pos));
            if (lt < NPC) {
                sts32(sb + SM_TDEG + (tile * 8 + k) * 4, deg);
                sts8(sb + SM_TNODE + tile * 8 + k, lt);
            }
        }
        TRACE(29);
        TRACE(30);
    }
    TRACE(31);
    __syncthreads();
    TRACE(32);
    bool slow = lds32(sb + SM_FLAG) != 0;

    constexpr uint32_t RD = SM_R1 - SM_R0;
    const uint32_t ring0 = sb + SM_R0 + w * STAGE;
    const char* tab_l = p.table + lane * 16;
    asm volatile("" : "+l"(tab_l));
    const char* e_l = (const char*)p.e_attr + (mi & 1) * 16;
    asm volatile("" : "+l"(e_l));
    const uint32_t cpo = lane * 16;
    const uint32_t elo = 4096 + rr * 32 + (((mi & 1) ^ ((rr >> 2) & 1)) << 4);
    const uint32_t lsrc = sb + SM_LSE + w * TCAP * 4, lid = sb + SM_LID + w * TCAP;
    const uint32_t lec = rr * 4;

    auto issue_full = [&](uint32_t lp, uint32_t dl) {
        const uint4 s0 = lds128(lp), s1 = lds128(lp + 16);
        const uint32_t eo = lds32(lp + lec);
        const uint32_t sv[8] = {s0.x, s0.y, s0.z, s0.w, s1.x, s1.y, s1.z, s1.w};
#pragma unroll
        for (int j = 0; j < 8; j++) cp16(ring0 + dl + (cpo ^ (j << 4)) + j * 512, madw(sv[j] & 0x3FFF, 512, tab_l));
        cp16(ring0 + dl + elo, madw(eo >> 14, 32, e_l));
    };
    auto issue0 = [&]() {
        const int cnt = lds32(sb + SM_TCNT + w * 4), nit = (cnt + 7) >> 3;
        if (nit > 0) {
            const int pad = nit * 8 - cnt;
            const uint4 s0 = lds128(lsrc), s1 = lds128(lsrc + 16);
            const uint32_t eo = lds32(lsrc + lec);
            const uint32_t sv[8] = {s0.x, s0.y, s0.z, s0.w, s1.x, s1.y, s1.z, s1.w};
#pragma unroll
            for (int j = 0; j < 8; j++) cp16z(ring0 + (cpo ^ (j << 4)) + j * 512, madw(sv[j] & 0x3FFF, 512, tab_l), (j >= pad) ? 16 : 0);
            cp16z(ring0 + elo, madw(eo >> 14, 32, e_l), (rr >= pad) ? 16 : 0);
        }
        cp_commit();
    };
    auto issue1 = [&]() {
        if ((int)lds32(sb + SM_TCNT + w * 4) > 8) issue_full(lsrc + 32, RD);
        cp_commit();
    };
    uint32_t bar_v = 0;
    bool over = false;
    if (tid == 0) asm volatile("ld.relaxed.gpu.global.u32 %0, [%1];" : "=r"(bar_v) : "l"(p.bar) : "memory");
    if (!slow) {
        const uint2 tn = lds64(sb + SM_TNODE + w * 8);
        const uint4 dg = lds128(sb + SM_TDEG + w * 32);
        const uint32_t p1 = dg.x, p2 = p1 + dg.y, p3 = p2 + dg.z, p4 = p3 + dg.w, tot = p4 + lds32(sb + SM_TDEG + w * 32 + 16);
        const uint32_t pad = (0u - tot) & 7u;
        if (lane == 0) sts32(sb + SM_TCNT + w * 4, tot);
        over = tot + pad > TCAP;
        uint32_t wd[TCAP / 32], sl[TCAP / 32];
#pragma unroll
        for (int r = 0; r < TCAP / 32; r++) {
            const uint32_t q = lane + 32 * r - pad;
            sl[r] = (q >= p1) + (q >= p2) + (q >= p3) + (q >= p4);
            const uint32_t pre = (q >= p4) ? p4 : ((q >= p3) ? p3 : ((q >= p2) ? p2 : ((q >= p1) ? p1 : 0)));
            const uint32_t node = prmt(tn.x, tn.y, sl[r]) & 0xFF;
            wd[r] = lds32(sb + SM_NL + ((q < tot) ? (node * NCAP + q - pre) * 4 : 0));
        }
#pragma unroll
        for (int r = 0; r < TCAP / 32; r++) {
            const uint32_t q = lane + 32 * r - pad;
            sts32(lsrc + (lane + 32 * r) * 4, (q < tot) ? wd[r] : 0);
            sts8(lid + lane + 32 * r, (q < tot) ? sl[r] * 16 : 0x7F);
        }
    }
    TRACE(10);
    if (tid == 0) {
        int it = 0;
        while ((int)(bar_v - bar_target) < 0 && ++it < SPIN_LIMIT)
            asm volatile("ld.relaxed.gpu.global.u32 %0, [%1];" : "=r"(bar_v) : "l"(p.bar) : "memory");
    }
    slow = __syncthreads_or(slow || over);
    TRACE(11);
    if (!slow) {
        issue0();
        issue1();
    } else {
        if (tid < NPC) sts8(sb + SM_TNODE + (tid & 15) * 8 + (tid >> 4), tid);
        __syncthreads();
    }
    TRACE(33);
    load_node_frags();
    TRACE(34);

    const uint32_t ldo = rr * 512 + ((mi ^ rr) << 4);
    const uint32_t sel = (g | ((8 | g) << 4) | (g << 8) | ((8 | g) << 12)) |
                         (((2 * t) | ((8 | (2 * t)) << 4) | ((2 * t + 1) << 8) | ((8 | (2 * t + 1)) << 12)) << 16);
    const uint32_t gg = (g * 16) | ((g * 16) << 16);
    const uint32_t tt = (t * 32) | ((t * 32 + 16) << 16);

    auto compute = [&](uint32_t st, uint32_t idp) {
        uint32_t eb[2];
        ldsm2(eb, st + elo);
        const uint2 iw = lds64(idp);
        const uint32_t sx = seteq_bf16x2(prmt(iw.x, iw.y, sel), tt);
        const uint32_t sa = seteq_bf16x2(prmt(iw.x, iw.y, sel >> 16), gg);
#pragma unroll
        for (int jj = 0; jj < 4; jj++) {
            uint32_t xb[4], hv[4];
            const uint32_t la = st + (ldo ^ ((jj & 1) << 6)) + (jj >> 1) * 128;
            ldsm4(xb, la);
            ldsm4t(hv, la + 256);
#pragma unroll
            for (int u = 0; u < 2; u++) {
                const int j = 2 * jj + u;
                float d[4];
                mma16816_z(d, Cf[j][0], Cf[j][1], Cf[j][2], Cf[j][3], eb[0], eb[1]);
                mma1688(d, xAf[j][0], xAf[j][1], sx);
                mma16816(d, ident, 0u, 0u, ident, xb[2 * u], xb[2 * u + 1]);
                const uint32_t m0 = fma_bf16x2(pack_bf16(tanh_ap(d[0]), tanh_ap(d[1])), hv[2 * u], hv[2 * u]);
                const uint32_t m1 = fma_bf16x2(pack_bf16(tanh_ap(d[2]), tanh_ap(d[3])), hv[2 * u + 1], hv[2 * u + 1]);
                mma1688(agg[j], m0, m1, sa);
            }
        }
    };

    const int nseg = slow ? NSEG : 1;
#pragma unroll 1
    for (int seg = 0; seg < nseg; seg++) {
        if (slow) {
            __syncthreads();
            if (tid < 16) sts32(sb + SM_TCNT + tid * 4, 0);
            __syncthreads();
            const int e = seg * TCAP + tid;
            int loc = -1; uint32_t r = 0;
            if (tid < TCAP && e < EE) {
                const int dd = __ldg(p.dst + e) - b * NPC;
                if (dd >= 0 && dd < NPC) { loc = dd; r = atoms_add(sb + SM_TCNT + (loc & 15) * 4, 1); }
            }
            __syncthreads();
            if (loc >= 0) {
                const uint32_t tile = loc & 15, tot = lds32(sb + SM_TCNT + tile * 4);
                const uint32_t pos = tile * TCAP + ((0u - tot) & 7u) + r;
                sts32(sb + SM_LSE + pos * 4, (uint32_t)__ldg(p.src + e) | ((uint32_t)e << 14));
                sts8(sb + SM_LID + pos, (loc >> 4) << 4);
            }
            const int pad = (0 - (int)lds32(sb + SM_TCNT + w * 4)) & 7;
            if (lane < pad) { sts8(sb + SM_LID + w * TCAP + lane, 0x7F); sts32(sb + SM_LSE + (w * TCAP + lane) * 4, 0); }
            __syncthreads();
            issue0();
            issue1();
        }
        const int nit = __shfl_sync(0xffffffffu, ((int)lds32(sb + SM_TCNT + w * 4) + 7) >> 3, 0);
        uint32_t st = ring0, so = ring0 + RD, lp = lsrc + 32, idp = lid;
        const uint32_t lend = lsrc + nit * 32;
        constexpr int AVG_NIT = (EE + NCTA * 128 - 1) / (NCTA * 128);
        constexpr int HEAVY = EE / NN * NPC * 207 / 200;
        const int ctot = __reduce_add_sync(0xffffffffu, (lane < 16) ? (int)lds32(sb + SM_TCNT + lane * 4) : 0);
        if (nit <= AVG_NIT && ctot <= HEAVY) {
#pragma unroll 1
            for (; lp <= lend; lp += 32, idp += 8) {
                if (idp == lid) cp_wait<1>(); else cp_wait<0>();
                __syncwarp();
                if (idp != lid && lp < lend) issue_full(lp, so - ring0);
                cp_commit();
                compute(st, idp);
                const uint32_t tmp = st; st = so; so = tmp;
            }
        } else {
#pragma unroll 1
            for (; lp <= lend; lp += 32, idp += 8) {
                cp_wait<1>();
                __syncwarp();
                compute(st, idp);
                __syncwarp();
                if (lp + 32 < lend) issue_full(lp + 32, st - ring0);
                cp_commit();
                const uint32_t tmp = st; st = so; so = tmp;
            }
        }
        cp_wait<0>();
        __syncwarp();
    }
    TRACE(35);

    {
        uint32_t o[8][2];
#pragma unroll
        for (int j = 0; j < 8; j++) {
            float v[4];
#pragma unroll
            for (int q = 0; q < 4; q++) { const float h = agg[j][q]; v[q] = fmaf(h, tanh_ap(h), h); }
            o[j][0] = pack_bf16(v[0], v[1]); o[j][1] = pack_bf16(v[2], v[3]);
        }
#pragma unroll
        for (int jp = 0; jp < 4; jp++) {
            const int c = 4 * jp + mi;
            stsm4t(ring0 + rr * 256 + ((c & 8) << 4) + (((c & 7) ^ rr) << 4), o[2 * jp][0], o[2 * jp][1], o[2 * jp + 1][0], o[2 * jp + 1][1]);
        }
        __syncwarp();
#pragma unroll
        for (int i = 0; i < 3; i++) {
            const int idx = lane + 32 * i, row = idx >> 4, c = idx & 15;
            const int nd = b * NPC + (int)lds8(sb + SM_TNODE + w * 8 + (row & 7));
            if (row < nslot && nd < NN) {
                const uint4 v = lds128(ring0 + row * 256 + ((c & 8) << 4) + (((c & 7) ^ row) << 4));
                *(uint4*)((char*)p.out + (size_t)nd * 256 + c * 16) = v;
            }
        }
    }
    TRACE(36);
}

__device__ __align__(16) bf16 g_fb_xa[NN * 128];
__device__ __align__(16) float g_fb_h[NN * 128];

__global__ void fb_node_kernel(const bf16* x, const bf16* uw, const bf16* vw, const bf16* gw, bf16* table) {
    __shared__ float xs[128];
    const int n = blockIdx.x, f = threadIdx.x;
    xs[f] = __bfloat162float(x[n * 128 + f]);
    __syncthreads();
    float a = 0.f, bb = 0.f, v = 0.f, u = 0.f;
    for (int k = 0; k < 128; k++) {
        const float xv = xs[k];
        a += xv * __bfloat162float(gw[k * 128 + f]);
        bb += xv * __bfloat162float(gw[(128 + k) * 128 + f]);
        v += xv * __bfloat162float(vw[k * 128 + f]);
        u += xv * __bfloat162float(uw[k * 128 + f]);
    }
    table[n * 256 + f] = __float2bfloat16(0.5f * bb);
    table[n * 256 + 128 + f] = __float2bfloat16(0.25f * v);
    g_fb_xa[n * 128 + f] = __float2bfloat16(0.5f * a);
    g_fb_h[n * 128 + f] = 0.5f * u;
}
__global__ void fb_edge_kernel(const bf16* e_attr, const int* src, const int* dst, const bf16* gw, const bf16* table) {
    const int e = blockIdx.x, f = threadIdx.x, s = src[e], d = dst[e];
    float z = 0.f;
    for (int k = 0; k < 16; k++) z += __bfloat162float(e_attr[e * 16 + k]) * __bfloat162float(gw[(256 + k) * 128 + f]);
    z = 0.5f * z + __bfloat162float(g_fb_xa[d * 128 + f]) + __bfloat162float(table[s * 256 + f]);
    const float hv = __bfloat162float(table[s * 256 + 128 + f]);
    atomicAdd(&g_fb_h[d * 128 + f], fmaf(hv, tanhf(z), hv));
}
__global__ void fb_out_kernel(bf16* out) {
    const int i = blockIdx.x * 128 + threadIdx.x;
    const float h = g_fb_h[i];
    out[i] = __float2bfloat16(fmaf(h, tanhf(h), h));
}

typedef CUresult (*EncodeFn)(CUtensorMap*, CUtensorMapDataType, cuuint32_t, void*, const cuuint64_t*, const cuuint64_t*,
                             const cuuint32_t*, const cuuint32_t*, CUtensorMapInterleave, CUtensorMapSwizzle,
                             CUtensorMapL2promotion, CUtensorMapFloatOOBfill);

static void make_map(EncodeFn enc, CUtensorMap* tm, const void* base, int rows, int cols, int box_rows) {
    cuuint64_t dims[2] = {(cuuint64_t)cols, (cuuint64_t)rows};
    cuuint64_t strides[1] = {(cuuint64_t)cols * 2};
    cuuint32_t box[2] = {64, (cuuint32_t)box_rows};
    cuuint32_t es[2] = {1, 1};
    enc(tm, CU_TENSOR_MAP_DATA_TYPE_BFLOAT16, 2, (void*)base, dims, strides, box, es, CU_TENSOR_MAP_INTERLEAVE_NONE,
        CU_TENSOR_MAP_SWIZZLE_128B, CU_TENSOR_MAP_L2_PROMOTION_NONE, CU_TENSOR_MAP_FLOAT_OOB_FILL_NONE);
}

}

extern "C" void kernel_launch(void* const* d_in, const int* in_sizes, int n_in, void* d_out, int out_size) {
    using namespace egc;
    (void)in_sizes; (void)n_in; (void)out_size;
    static EncodeFn enc = nullptr;
    static void* table = nullptr;
    static void* xch = nullptr;
    static void* bar = nullptr;
    static bool persistent = false;
    if (!enc) {
        void* fn = nullptr;
        cudaDriverEntryPointQueryResult qr;
        cudaGetDriverEntryPoint("cuTensorMapEncodeTiled", &fn, cudaEnableDefault, &qr);
        enc = (EncodeFn)fn;
        cudaGetSymbolAddress(&table, g_table);
        cudaGetSymbolAddress(&xch, g_xch);
        cudaGetSymbolAddress(&bar, g_bar);
        cudaFuncSetAttribute(egc_kernel, cudaFuncAttributeMaxDynamicSharedMemorySize, SMEM_BYTES);
        int dev = 0, sms = 0, per_sm = 0;
        cudaGetDevice(&dev);
        cudaDeviceGetAttribute(&sms, cudaDevAttrMultiProcessorCount, dev);
        cudaOccupancyMaxActiveBlocksPerMultiprocessor(&per_sm, egc_kernel, NTHR, SMEM_BYTES);
        persistent = enc != nullptr && sms * per_sm >= NCTA;
    }
    if (!persistent) {
        const bf16* x = (const bf16*)d_in[0];
        fb_node_kernel<<<NN, 128, 0, cudaStreamPerThread>>>(x, (const bf16*)d_in[4], (const bf16*)d_in[5], (const bf16*)d_in[6], (bf16*)table);
        fb_edge_kernel<<<EE, 128, 0, cudaStreamPerThread>>>((const bf16*)d_in[1], (const int*)d_in[2], (const int*)d_in[3], (const bf16*)d_in[6], (const bf16*)table);
        fb_out_kernel<<<NN, 128, 0, cudaStreamPerThread>>>((bf16*)d_out);
        return;
    }
    CUtensorMap tm_x, tm_g, tm_u, tm_v, tm_t;
    make_map(enc, &tm_x, d_in[0], NN, 128, 80);
    make_map(enc, &tm_u, d_in[4], 128, 128, 128);
    make_map(enc, &tm_v, d_in[5], 128, 128, 128);
    make_map(enc, &tm_g, d_in[6], 272, 128, 128);
    make_map(enc, &tm_t, table, NN, 256, NPC);
    Params p;
    p.e_attr = (const bf16*)d_in[1];
    p.src = (const int*)d_in[2];
    p.dst = (const int*)d_in[3];
    p.gw = (const bf16*)d_in[6];
    p.out = (bf16*)d_out;
    p.bar = (unsigned*)bar;
    p.xch = (uint4*)xch;
    p.table = (const char*)table;
    egc_kernel<<<NCTA, NTHR, SMEM_BYTES, cudaStreamPerThread>>>(p, tm_x, tm_g, tm_u, tm_v, tm_t);
}
```

```cpp
#include <cuda_runtime.h>
#include <cuda_bf16.h>
#include <cuda.h>
#include <stdint.h>
#include <type_traits>

namespace egc {

typedef __nv_bfloat16 bf16;

constexpr int NN = 10000, EE = 160000;
constexpr int NCTA = 132, NPC = 76, ECH = 1216, NTHR = 512;
constexpr int PIECES = 10, XCAP = 3 * PIECES;
constexpr int TCAP = 96;
constexpr int NSEG = (EE + TCAP - 1) / TCAP;
constexpr int SPIN_LIMIT = 1 << 20;
constexpr uint32_t START_DELAY = 550;

constexpr int STAGE = 4352;
constexpr int SM_R0 = 0;
constexpr int SM_R1 = 16 * STAGE;
constexpr int SM_S = SM_R1;
constexpr int SM_WU = SM_R1 + 8 * STAGE;
constexpr int SM_WA = SM_R1 + 16 * STAGE;
constexpr int SM_X = SM_WA + 32768;
constexpr int SM_C = SM_X + 20480;
constexpr int SM_LSE = SM_C + 4096;
constexpr int SM_LID = SM_LSE + 6144 + 128;
constexpr int SM_HIST = SM_LID + 1536 + 32;
constexpr int SM_KEYS = SM_HIST + 544;
constexpr int SM_CURS = SM_KEYS + 512;
constexpr int SM_DBIN = SM_CURS + 512;
constexpr int SM_TDEG = SM_DBIN + 256;
constexpr int SM_TNODE = SM_TDEG + 512;
constexpr int SM_TCNT = SM_TNODE + 128;
constexpr int SM_FLAG = SM_TCNT + 64;
constexpr int NCAP = 40;
constexpr int SM_NL = SM_FLAG + 16;
constexpr int SM_BAR = SM_NL + NPC * NCAP * 4 + 128;
constexpr int SM_TRACE = SM_BAR + 9 * 8 + 8;
constexpr int SM_END = SM_TRACE + 2 * 48 * 4;
constexpr int SMEM_BYTES = SM_END + 1024;

__device__ __align__(1024) uint4 g_table[NN * 32];
__device__ __align__(1024) uint4 g_xch[NCTA * NCTA * PIECES];
__device__ __align__(128) unsigned g_bar[32];
#define TRACE(i) do {} while (0)

__device__ __forceinline__ void mma16816(float* d, uint32_t a0, uint32_t a1, uint32_t a2, uint32_t a3, uint32_t b0, uint32_t b1) {
    asm("mma.sync.aligned.m16n8k16.row.col.f32.bf16.bf16.f32 {%0,%1,%2,%3}, {%4,%5,%6,%7}, {%8,%9}, {%0,%1,%2,%3};"
        : "+f"(d[0]), "+f"(d[1]), "+f"(d[2]), "+f"(d[3]) : "r"(a0), "r"(a1), "r"(a2), "r"(a3), "r"(b0), "r"(b1));
}
__device__ __forceinline__ void mma16816_z(float* d, uint32_t a0, uint32_t a1, uint32_t a2, uint32_t a3, uint32_t b0, uint32_t b1) {
    asm("mma.sync.aligned.m16n8k16.row.col.f32.bf16.bf16.f32 {%0,%1,%2,%3}, {%4,%5,%6,%7}, {%8,%9}, {%10,%10,%10,%10};"
        : "=f"(d[0]), "=f"(d[1]), "=f"(d[2]), "=f"(d[3]) : "r"(a0), "r"(a1), "r"(a2), "r"(a3), "r"(b0), "r"(b1), "f"(0.f));
}
__device__ __forceinline__ void mma1688(float* d, uint32_t a0, uint32_t a1, uint32_t b0) {
    asm("mma.sync.aligned.m16n8k8.row.col.f32.bf16.bf16.f32 {%0,%1,%2,%3}, {%4,%5}, {%6}, {%0,%1,%2,%3};"
        : "+f"(d[0]), "+f"(d[1]), "+f"(d[2]), "+f"(d[3]) : "r"(a0), "r"(a1), "r"(b0));
}
__device__ __forceinline__ void mma1688_z(float* d, uint32_t a0, uint32_t a1, uint32_t b0) {
    asm("mma.sync.aligned.m16n8k8.row.col.f32.bf16.bf16.f32 {%0,%1,%2,%3}, {%4,%5}, {%6}, {%7,%7,%7,%7};"
        : "=f"(d[0]), "=f"(d[1]), "=f"(d[2]), "=f"(d[3]) : "r"(a0), "r"(a1), "r"(b0), "f"(0.f));
}
__device__ __forceinline__ void ldsm4(uint32_t* r, uint32_t addr) {
    asm volatile("ldmatrix.sync.aligned.m8n8.x4.shared.b16 {%0,%1,%2,%3}, [%4];" : "=r"(r[0]), "=r"(r[1]), "=r"(r[2]), "=r"(r[3]) : "r"(addr) : "memory");
}
__device__ __forceinline__ void ldsm4t(uint32_t* r, uint32_t addr) {
    asm volatile("ldmatrix.sync.aligned.m8n8.x4.trans.shared.b16 {%0,%1,%2,%3}, [%4];" : "=r"(r[0]), "=r"(r[1]), "=r"(r[2]), "=r"(r[3]) : "r"(addr) : "memory");
}
__device__ __forceinline__ void ldsm2(uint32_t* r, uint32_t addr) {
    asm volatile("ldmatrix.sync.aligned.m8n8.x2.shared.b16 {%0,%1}, [%2];" : "=r"(r[0]), "=r"(r[1]) : "r"(addr) : "memory");
}
__device__ __forceinline__ void stsm4t(uint32_t addr, uint32_t r0, uint32_t r1, uint32_t r2, uint32_t r3) {
    asm volatile("stmatrix.sync.aligned.m8n8.x4.trans.shared.b16 [%0], {%1,%2,%3,%4};" :: "r"(addr), "r"(r0), "r"(r1), "r"(r2), "r"(r3) : "memory");
}
__device__ __forceinline__ float tanh_ap(float x) { float r; asm("tanh.approx.f32 %0, %1;" : "=f"(r) : "f"(x)); return r; }
__device__ __forceinline__ uint32_t pack_bf16(float lo, float hi) { uint32_t r; asm("cvt.rn.bf16x2.f32 %0, %1, %2;" : "=r"(r) : "f"(hi), "f"(lo)); return r; }
__device__ __forceinline__ uint32_t fma_bf16x2(uint32_t a, uint32_t b, uint32_t c) { uint32_t r; asm("fma.rn.bf16x2 %0, %1, %2, %3;" : "=r"(r) : "r"(a), "r"(b), "r"(c)); return r; }
__device__ __forceinline__ uint32_t mul_bf16x2(uint32_t a, uint32_t b) { uint32_t r; asm("mul.rn.bf16x2 %0, %1, %2;" : "=r"(r) : "r"(a), "r"(b)); return r; }
__device__ __forceinline__ uint32_t seteq_bf16x2(uint32_t a, uint32_t b) { uint32_t r; asm("set.eq.bf16x2.bf16x2 %0, %1, %2;" : "=r"(r) : "r"(a), "r"(b)); return r; }
__device__ __forceinline__ uint32_t prmt(uint32_t a, uint32_t b, uint32_t s) { uint32_t r; asm("prmt.b32 %0, %1, %2, %3;" : "=r"(r) : "r"(a), "r"(b), "r"(s)); return r; }
__device__ __forceinline__ uint32_t shl_clamp(uint32_t a, uint32_t s) { uint32_t r; asm("shl.b32 %0, %1, %2;" : "=r"(r) : "r"(a), "r"(s)); return r; }
__device__ __forceinline__ void cp16(uint32_t dst, const void* src) { asm volatile("cp.async.cg.shared.global [%0], [%1], 16;" :: "r"(dst), "l"(src) : "memory"); }
__device__ __forceinline__ void cp16z(uint32_t dst, const void* src, uint32_t sz) { asm volatile("cp.async.cg.shared.global [%0], [%1], 16, %2;" :: "r"(dst), "l"(src), "r"(sz) : "memory"); }
__device__ __forceinline__ const void* madw(uint32_t a, uint32_t m, const void* base) {
    const void* r; asm("mad.wide.u32 %0, %1, %2, %3;" : "=l"(r) : "r"(a), "r"(m), "l"(base)); return r;
}
__device__ __forceinline__ void cp16_p(bool p, uint32_t dst, const void* src) {
    asm volatile("{\n.reg .pred p;\nsetp.ne.u32 p, %2, 0;\n@p cp.async.cg.shared.global [%0], [%1], 16;\n}" :: "r"(dst), "l"(src), "r"((uint32_t)p) : "memory");
}
__device__ __forceinline__ void cp_commit() { asm volatile("cp.async.commit_group;" ::: "memory"); }
template <int N> __device__ __forceinline__ void cp_wait() { asm volatile("cp.async.wait_group %0;" :: "n"(N) : "memory"); }
__device__ __forceinline__ uint4 lds128(uint32_t a) { uint4 v; asm volatile("ld.shared.v4.u32 {%0,%1,%2,%3}, [%4];" : "=r"(v.x), "=r"(v.y), "=r"(v.z), "=r"(v.w) : "r"(a) : "memory"); return v; }
__device__ __forceinline__ uint2 lds64(uint32_t a) { uint2 v; asm volatile("ld.shared.v2.u32 {%0,%1}, [%2];" : "=r"(v.x), "=r"(v.y) : "r"(a) : "memory"); return v; }
__device__ __forceinline__ uint32_t lds32(uint32_t a) { uint32_t v; asm volatile("ld.shared.u32 %0, [%1];" : "=r"(v) : "r"(a) : "memory"); return v; }
__device__ __forceinline__ uint32_t lds8(uint32_t a) { uint32_t v; asm volatile("ld.shared.u8 %0, [%1];" : "=r"(v) : "r"(a) : "memory"); return v; }
__device__ __forceinline__ void sts32(uint32_t a, uint32_t v) { asm volatile("st.shared.u32 [%0], %1;" :: "r"(a), "r"(v) : "memory"); }
__device__ __forceinline__ void sts8(uint32_t a, uint32_t v) { asm volatile("st.shared.u8 [%0], %1;" :: "r"(a), "r"(v) : "memory"); }
__device__ __forceinline__ void sts128(uint32_t a, uint4 v) { asm volatile("st.shared.v4.u32 [%0], {%1,%2,%3,%4};" :: "r"(a), "r"(v.x), "r"(v.y), "r"(v.z), "r"(v.w) : "memory"); }
__device__ __forceinline__ uint32_t atoms_add(uint32_t a, uint32_t v) { uint32_t r; asm volatile("atom.shared.add.u32 %0, [%1], %2;" : "=r"(r) : "r"(a), "r"(v) : "memory"); return r; }
__device__ __forceinline__ void reds_add(uint32_t a, uint32_t v) { asm volatile("red.shared.add.u32 [%0], %1;" :: "r"(a), "r"(v) : "memory"); }
__device__ __forceinline__ uint32_t atoms_add_p(bool p, uint32_t a, uint32_t v) {
    uint32_t r = 0;
    asm volatile("{\n.reg .pred p;\nsetp.ne.u32 p, %3, 0;\n@p atom.shared.add.u32 %0, [%1], %2;\n}" : "+r"(r) : "r"(a), "r"(v), "r"((uint32_t)p) : "memory");
    return r;
}
__device__ __forceinline__ uint32_t lds32_p(bool p, uint32_t a) {
    uint32_t r = 0;
    asm volatile("{\n.reg .pred p;\nsetp.ne.u32 p, %2, 0;\n@p ld.shared.u32 %0, [%1];\n}" : "+r"(r) : "r"(a), "r"((uint32_t)p) : "memory");
    return r;
}
__device__ __forceinline__ void sts32_p(bool p, uint32_t a, uint32_t v) {
    asm volatile("{\n.reg .pred p;\nsetp.ne.u32 p, %2, 0;\n@p st.shared.u32 [%0], %1;\n}" :: "r"(a), "r"(v), "r"((uint32_t)p) : "memory");
}
__device__ __forceinline__ void sts8_p(bool p, uint32_t a, uint32_t v) {
    asm volatile("{\n.reg .pred p;\nsetp.ne.u32 p, %2, 0;\n@p st.shared.u8 [%0], %1;\n}" :: "r"(a), "r"(v), "r"((uint32_t)p) : "memory");
}
__device__ __forceinline__ void st_piece(uint4* p, uint4 v) {
    asm volatile("{\n.reg .b128 q;\n.reg .b64 lo, hi;\nmov.b64 lo, {%1,%2};\nmov.b64 hi, {%3,%4};\nmov.b128 q, {lo, hi};\nst.relaxed.gpu.global.b128 [%0], q;\n}"
                 :: "l"(p), "r"(v.x), "r"(v.y), "r"(v.z), "r"(v.w) : "memory");
}
__device__ __forceinline__ uint4 ld_piece(const uint4* p) {
    uint4 v;
    asm volatile("{\n.reg .b128 q;\n.reg .b64 lo, hi;\nld.relaxed.gpu.global.b128 q, [%4];\nmov.b128 {lo, hi}, q;\nmov.b64 {%0,%1}, lo;\nmov.b64 {%2,%3}, hi;\n}"
                 : "=r"(v.x), "=r"(v.y), "=r"(v.z), "=r"(v.w) : "l"(p) : "memory");
    return v;
}
__device__ __forceinline__ void mbar_init(uint32_t bar, uint32_t cnt) { asm volatile("mbarrier.init.shared::cta.b64 [%0], %1;" :: "r"(bar), "r"(cnt) : "memory"); }
__device__ __forceinline__ void mbar_expect(uint32_t bar, uint32_t bytes) { asm volatile("mbarrier.arrive.expect_tx.shared::cta.b64 _, [%0], %1;" :: "r"(bar), "r"(bytes) : "memory"); }
__device__ __forceinline__ void mbar_wait(uint32_t bar, uint32_t parity) {
    uint32_t ok; int it = 0;
    do {
        asm volatile("{\n.reg .pred p;\nmbarrier.try_wait.parity.shared::cta.b64 p, [%1], %2;\nselp.u32 %0, 1, 0, p;\n}" : "=r"(ok) : "r"(bar), "r"(parity) : "memory");
    } while (!ok && ++it < (1 << 22));
}
__device__ __forceinline__ void tma_load2d(uint32_t dst, const CUtensorMap* tm, int c0, int c1, uint32_t bar) {
    asm volatile("cp.async.bulk.tensor.2d.shared::cluster.global.mbarrier::complete_tx::bytes [%0], [%1, {%3, %4}], [%2];"
                 :: "r"(dst), "l"(tm), "r"(bar), "r"(c0), "r"(c1) : "memory");
}
__device__ __forceinline__ void tma_load2d_mc(uint32_t dst, const CUtensorMap* tm, int c0, int c1, uint32_t bar) {
    asm volatile("cp.async.bulk.tensor.2d.shared::cluster.global.mbarrier::complete_tx::bytes.multicast::cluster [%0], [%1, {%3, %4}], [%2], %5;"
                 :: "r"(dst), "l"(tm), "r"(bar), "r"(c0), "r"(c1), "h"((uint16_t)3) : "memory");
}
__device__ __forceinline__ void tma_store2d(const CUtensorMap* tm, int c0, int c1, uint32_t src) {
    asm volatile("cp.async.bulk.tensor.2d.global.shared::cta.bulk_group [%0, {%2, %3}], [%1];"
                 :: "l"(tm), "r"(src), "r"(c0), "r"(c1) : "memory");
}
__device__ __forceinline__ void spin(uint32_t cycles) {
    uint32_t c0, c1;
    asm volatile("mov.u32 %0, %%clock;" : "=r"(c0));
    do { asm volatile("mov.u32 %0, %%clock;" : "=r"(c1)); } while (c1 - c0 < cycles);
}
__device__ __forceinline__ void lt_bar() { asm volatile("bar.sync 3, 256;" ::: "memory"); }
__device__ __forceinline__ void wg_bar(int id) { asm volatile("bar.sync %0, 128;" :: "r"(id) : "memory"); }

__device__ __forceinline__ void wgmma_n80(float (&d)[40], uint64_t da, uint64_t db, int acc) {
    asm volatile("{\n.reg .pred p;\nsetp.ne.b32 p, %42, 0;\n"
        "wgmma.mma_async.sync.aligned.m64n80k16.f32.bf16.bf16 "
        "{%0,%1,%2,%3,%4,%5,%6,%7,%8,%9,%10,%11,%12,%13,%14,%15,%16,%17,%18,%19,"
        "%20,%21,%22,%23,%24,%25,%26,%27,%28,%29,%30,%31,%32,%33,%34,%35,%36,%37,%38,%39}, "
        "%40, %41, p, 1, 1, 1, 0;\n}\n"
        : "+f"(d[0]), "+f"(d[1]), "+f"(d[2]), "+f"(d[3]), "+f"(d[4]), "+f"(d[5]), "+f"(d[6]), "+f"(d[7]), "+f"(d[8]), "+f"(d[9]),
          "+f"(d[10]), "+f"(d[11]), "+f"(d[12]), "+f"(d[13]), "+f"(d[14]), "+f"(d[15]), "+f"(d[16]), "+f"(d[17]), "+f"(d[18]), "+f"(d[19]),
          "+f"(d[20]), "+f"(d[21]), "+f"(d[22]), "+f"(d[23]), "+f"(d[24]), "+f"(d[25]), "+f"(d[26]), "+f"(d[27]), "+f"(d[28]), "+f"(d[29]),
          "+f"(d[30]), "+f"(d[31]), "+f"(d[32]), "+f"(d[33]), "+f"(d[34]), "+f"(d[35]), "+f"(d[36]), "+f"(d[37]), "+f"(d[38]), "+f"(d[39])
        : "l"(da), "l"(db), "r"(acc));
}

__device__ __forceinline__ void gemm_issue(float (&d)[40], uint32_t wbase, uint32_t xbase) {
    asm volatile("wgmma.fence.sync.aligned;" ::: "memory");
#pragma unroll
    for (int s = 0; s < 8; s++) {
        const uint32_t aa = wbase + s * 2048, ab = xbase + (s >> 2) * 10240 + (s & 3) * 32;
        const uint64_t da = (uint64_t)((aa & 0x3FFFF) >> 4) | ((uint64_t)64 << 16) | ((uint64_t)64 << 32) | ((uint64_t)1 << 62);
        const uint64_t db = (uint64_t)((ab & 0x3FFFF) >> 4) | ((uint64_t)1 << 16) | ((uint64_t)64 << 32) | ((uint64_t)1 << 62);
        wgmma_n80(d, da, db, s > 0);
    }
    asm volatile("wgmma.commit_group.sync.aligned;" ::: "memory");
}
__device__ __forceinline__ void gemm_wait(float (&d)[40]) {
    asm volatile("wgmma.wait_group.sync.aligned 0;" ::: "memory");
#pragma unroll
    for (int i = 0; i < 40; i++) asm volatile("" : "+f"(d[i]) :: "memory");
}
__device__ __forceinline__ void gemm_store(const float (&d)[40], float sc, uint32_t base, int w4, int lane) {
    const int mi = lane >> 3, rr = lane & 7;
    const uint32_t sa = base + (rr + 8 * (mi >> 1)) * 128 + (((2 * w4 + (mi & 1)) ^ rr) << 4);
#pragma unroll
    for (int p = 0; p < 5; p++) {
        const float* q = d + 8 * p;
        stsm4t(sa + p * 2048, pack_bf16(q[0] * sc, q[1] * sc), pack_bf16(q[2] * sc, q[3] * sc),
               pack_bf16(q[4] * sc, q[5] * sc), pack_bf16(q[6] * sc, q[7] * sc));
    }
}

struct Params {
    const int* dst;
    const int* src;
    unsigned* bar;
    uint4* xch;
    const bf16* gw;
    const bf16* e_attr;
    const char* table;
    bf16* out;
};

__global__ void __launch_bounds__(NTHR, 1)
egc_kernel(const Params p, const __grid_constant__ CUtensorMap tm_x, const __grid_constant__ CUtensorMap tm_g,
           const __grid_constant__ CUtensorMap tm_u, const __grid_constant__ CUtensorMap tm_v, const __grid_constant__ CUtensorMap tm_t) {
    extern __shared__ unsigned char smem_raw[];
    const uint32_t sb = ((uint32_t)__cvta_generic_to_shared(smem_raw) + 1023u) & ~1023u;
    const int tid = threadIdx.x, lane = tid & 31, b = blockIdx.x;
    const int w = __shfl_sync(0xffffffffu, tid >> 5, 0);
    const int wq = w >> 2, w4 = w & 3;
    const int g = lane >> 2, t = lane & 3, mi = lane >> 3, rr = lane & 7;
    TRACE(0);

    uint32_t Cf[8][4];
    auto load_cf = [&]() {
        const int krow = rr + 8 * (mi >> 1);
#pragma unroll
        for (int j = 0; j < 8; j++) {
            const int c = 2 * j + (mi & 1);
            ldsm4t(Cf[j], sb + SM_C + krow * 256 + ((c & 8) << 4) + (((c & 7) ^ rr) << 4));
#pragma unroll
            for (int q = 0; q < 4; q++) Cf[j][q] = mul_bf16x2(Cf[j][q], 0x3F003F00u);
        }
    };
    uint32_t xAf[8][2];
    float agg[8][4];
    const uint32_t ident = (g == 2 * t) ? 0x3F80u : ((g == 2 * t + 1) ? 0x3F800000u : 0u);
    const int nslot = (w < 12) ? 5 : 4;
    auto load_node_frags = [&]() {
        const int mynode = lds8(sb + SM_TNODE + w * 8 + ((rr < nslot) ? rr : 0));
#pragma unroll
        for (int jp = 0; jp < 4; jp++) {
            const int c = 4 * jp + mi;
            const uint32_t off = mynode * 128 + (((c & 7) ^ (mynode & 7)) << 4);
            uint32_t q[4];
            ldsm4t(q, sb + SM_WA + (c >> 3) * 16384 + off);
            xAf[2 * jp][0] = q[0]; xAf[2 * jp][1] = q[1]; xAf[2 * jp + 1][0] = q[2]; xAf[2 * jp + 1][1] = q[3];
            ldsm4t(q, sb + SM_X + (c >> 3) * 10240 + off);
            mma1688_z(agg[2 * jp], q[0], q[1], ident);
            mma1688_z(agg[2 * jp + 1], q[2], q[3], ident);
        }
    };
    uint32_t bar_target = 0;
    constexpr int LT = 256;
    int ed[3], es[3];
    uint32_t epoch;
#pragma unroll
    for (int m = 0; m < 3; m++) {
        const int k = tid + m * NTHR, e = b * ECH + k;
        ed[m] = ((k < ECH) && (e < EE)) ? __ldg(p.dst + e) : -1;
    }
#pragma unroll
    for (int m = 0; m < 3; m++) {
        const int k = tid + m * NTHR, e = b * ECH + k;
        es[m] = ((k < ECH) && (e < EE)) ? __ldg(p.src + e) : 0;
    }
    asm volatile("ld.relaxed.gpu.global.u32 %0, [%1];" : "=r"(epoch) : "l"(p.bar) : "memory");
    if (wq >= 2) {
        const int lt = tid - LT;
        if (lt < 136) sts32(sb + SM_HIST + lt * 4, 0);
        if (lt < 128) { sts32(sb + SM_KEYS + lt * 4, 0); sts32(sb + SM_TDEG + lt * 4, 0); }
        if (lt < 64) sts32(sb + SM_DBIN + lt * 4, 0);
        if (lt == 0) sts32(sb + SM_FLAG, 0);
    } else {
        {
            const int r = tid >> 4, c = tid & 15;
            cp16(sb + SM_C + r * 256 + ((c & 8) << 4) + (((c & 7) ^ (r & 7)) << 4), p.gw + (256 + r) * 128 + c * 8);
        }
        if (tid == 0) {
            for (int i = 0; i < 9; i++) mbar_init(sb + SM_BAR + i * 8, 1);
            asm volatile("fence.mbarrier_init.release.cluster;" ::: "memory");
            const uint32_t bx = sb + SM_BAR;
            mbar_expect(bx, 20480);
#pragma unroll
            for (int i = 0; i < 8; i++) mbar_expect(bx + 8 + i * 8, 16384);
            spin(START_DELAY);
            tma_load2d(sb + SM_X, &tm_x, 0, b * NPC, bx);
            tma_load2d(sb + SM_X + 10240, &tm_x, 64, b * NPC, bx);
            tma_load2d(sb + SM_R0, &tm_g, 0, 128, bx + 8);
            tma_load2d(sb + SM_R0 + 16384, &tm_g, 64, 128, bx + 16);
            tma_load2d(sb + SM_R0 + 2 * 16384, &tm_v, 0, 0, bx + 24);
            tma_load2d(sb + SM_R0 + 3 * 16384, &tm_v, 64, 0, bx + 32);
        }
    }
    cp_commit();
    __syncthreads();
    TRACE(24);
    {
        uint32_t jj[3], rk[3];
#pragma unroll
        for (int m = 0; m < 3; m++) {
            jj[m] = (ed[m] >= 0) ? (((uint32_t)ed[m] * 55189u) >> 22) : (132 + (lane & 3));
            rk[m] = atoms_add(sb + SM_HIST + jj[m] * 4, 1);
        }
#pragma unroll
        for (int m = 0; m < 3; m++) {
            const uint32_t loc = (uint32_t)ed[m] - jj[m] * NPC;
            const uint32_t q = (rk[m] * 43691u) >> 17;
            const uint32_t off = jj[m] * (PIECES * 16) + q * 16 + (rk[m] - 3 * q + 1) * 4;
            sts32(sb + SM_S + ((ed[m] >= 0 && rk[m] < XCAP) ? off : NCTA * PIECES * 16 + lane * 4),
                  (uint32_t)es[m] | (loc << 14) | ((uint32_t)(tid + m * NTHR) << 21));
        }
    }
    const uint32_t bar_q = epoch / (2 * NCTA);
    epoch = (bar_q + 1) & 0xFFFFFF;
    cp_wait<0>();
    TRACE(25);
    __syncthreads();
    {
        uint4 v[3]; uint32_t c[3];
#pragma unroll
        for (int m = 0; m < 3; m++) {
            const int pc = min(tid + m * NTHR, NCTA * PIECES - 1);
            v[m] = lds128(sb + SM_S + pc * 16);
            c[m] = lds32(sb + SM_HIST + ((pc * 6554) >> 16) * 4);
        }
#pragma unroll
        for (int m = 0; m < 3; m++) {
            const int pc = tid + m * NTHR;
            const int j = (pc * 6554) >> 16, q = pc - j * PIECES;
            if ((m < 2 || pc < NCTA * PIECES) && (q < 4 || c[m] > 3 * (q & ~1) || b >= 128)) {
                v[m].x = (epoch << 8) | min(c[m], 255u);
                st_piece(p.xch + (((j * (PIECES / 2) + (q >> 1)) * NCTA + b) * 2 + (q & 1)), v[m]);
            }
        }
    }
    TRACE(46);
    __syncthreads();
    if (tid == LT) asm volatile("red.relaxed.gpu.global.add.u32 [%0], 1;" :: "l"(p.bar + 1) : "memory");
    load_cf();
    if (wq < 2) {
        float d[40];
        const uint32_t xt = sb + SM_X;
        const bool elect = (w4 == 0 && lane == 0);
        mbar_wait(sb + SM_BAR, 0);
#pragma unroll 1
        for (int r = 0; r < 4; r++) {
            const uint32_t wt = sb + ((r < 2) ? SM_R0 + r * 32768 : ((r == 2) ? SM_WA : SM_WU)) + wq * 16384;
            mbar_wait(sb + SM_BAR + 8 + (2 * r + wq) * 8, 0);
            TRACE(2 + 2 * r);
            gemm_issue(d, wt, xt);
            if (r == 0 && tid == 0) {
#pragma unroll
                for (int i = 0; i < 2; i++) {
                    tma_load2d(sb + SM_WA + i * 16384, &tm_g, i * 64, 0, sb + SM_BAR + 8 + (4 + i) * 8);
                    tma_load2d(sb + SM_WU + i * 16384, &tm_u, i * 64, 0, sb + SM_BAR + 8 + (6 + i) * 8);
                }
            }
            if (r == 2) {
                if (elect) {
                    asm volatile("cp.async.bulk.wait_group 0;" ::: "memory");
                    asm volatile("fence.proxy.async.global;" ::: "memory");
                    asm volatile("red.relaxed.gpu.global.add.u32 [%0], 1;" :: "l"(p.bar) : "memory");
                }
            }
            if (r == 3 && tid == 0) {
                const int e0 = b * ECH, ne = min(ECH, EE - e0);
                asm volatile("cp.async.bulk.prefetch.L2.global [%0], %1;" :: "l"(p.e_attr + (size_t)e0 * 16), "r"(ne * 32) : "memory");
            }
            __syncwarp();
            gemm_wait(d);
            if (r < 3) wg_bar(1 + wq); else asm volatile("bar.sync 6, 256;" ::: "memory");
            gemm_store(d, (r == 1) ? 0.25f : 0.5f, (r < 3) ? wt : xt + wq * 10240, w4, lane);
            if (r < 2) {
                asm volatile("fence.proxy.async.shared::cta;" ::: "memory");
                wg_bar(1 + wq);
                if (elect) {
                    tma_store2d(&tm_t, (2 * r + wq) * 64, b * NPC, wt);
                    asm volatile("cp.async.bulk.commit_group;" ::: "memory");
                }
                __syncwarp();
            }
            TRACE(3 + 2 * r);
        }

        bar_target = (bar_q + 1) * (2 * NCTA);
        TRACE(9);
    } else {
        const int lt = tid - LT;
        if (lt == 0) {
            uint32_t v; int it = 0;
            const uint32_t target = bar_q * NCTA + NCTA / 2;
            do { asm volatile("ld.relaxed.gpu.global.u32 %0, [%1];" : "=r"(v) : "l"(p.bar + 1) : "memory"); }
            while ((int)(v - target) < 0 && ++it < SPIN_LIMIT);
        }
        lt_bar();
        TRACE(26);
        uint4 pv[6];
        const int pi5 = 128 + ((lt >> 1) & 3), pq5 = 2 * (lt >> 3) + (lt & 1);
        const uint4* px0 = p.xch + b * (NCTA * PIECES) + lt;
        const uint4* px5 = p.xch + b * (NCTA * PIECES) + (lt >> 3) * (2 * NCTA) + 256 + (lt & 7);
        const uint32_t tg = epoch << 8;
        auto fetch = [&](const uint4* a) {
            uint4 v = ld_piece(a);
            int it = 0;
            while (((v.x ^ tg) >> 8) && ++it < SPIN_LIMIT) { __nanosleep(100); v = ld_piece(a); }
            return v;
        };
        pv[0] = ld_piece(px0);
        pv[1] = ld_piece(px0 + 2 * NCTA);
        pv[5] = (lt < 4 * PIECES) ? ld_piece(px5) : make_uint4(tg, 0, 0, 0);
        for (int it = 0; (((pv[0].x ^ tg) | (pv[1].x ^ tg) | (pv[5].x ^ tg)) >> 8) && it < SPIN_LIMIT; it++) {
            __nanosleep(100);
            if ((pv[0].x ^ tg) >> 8) pv[0] = ld_piece(px0);
            if ((pv[1].x ^ tg) >> 8) pv[1] = ld_piece(px0 + 2 * NCTA);
            if ((pv[5].x ^ tg) >> 8) pv[5] = ld_piece(px5);
        }
        const int cnt = pv[0].x & 255, cnt5 = pv[5].x & 255;
#pragma unroll
        for (int m = 2; m < 5; m++) pv[m] = (cnt > 6 * m) ? ld_piece(px0 + m * (2 * NCTA)) : make_uint4(tg, 0, 0, 0);
        if (cnt > XCAP || cnt5 > XCAP) sts32(sb + SM_FLAG, 1);
        TRACE(27);
        const uint32_t dmy = (96 + lane) * 4;
        uint32_t ao[9], rk[9];
        auto count = [&](int m, int o) {
            const int nv = (m < 5) ? cnt - 3 * (2 * m + (lt & 1)) : cnt5 - 3 * pq5;
#pragma unroll
            for (int s = 0; s < 3; s++) {
                const uint32_t pl = (s == 0) ? pv[m].y : ((s == 1) ? pv[m].z : pv[m].w);
                ao[o + s] = (nv > s) ? ((pl >> 12) & 0x1FC) : dmy;
                rk[o + s] = atoms_add(sb + SM_KEYS + ao[o + s], 1);
            }
        };
        auto put = [&](int m, int o) {
            const uint32_t e0s = (uint32_t)(((m < 5) ? (lt >> 1) : pi5) * ECH) << 14;
#pragma unroll
            for (int s = 0; s < 3; s++) {
                const uint32_t pl = (s == 0) ? pv[m].y : ((s == 1) ? pv[m].z : pv[m].w);
                const bool ok = ao[o + s] < 96 * 4 && rk[o + s] < NCAP;
                sts32(sb + SM_NL + (ok ? ao[o + s] * NCAP + rk[o + s] * 4 : NPC * NCAP * 4 + lane * 4), (pl & 0x3FFF) + ((pl >> 21) << 14) + e0s);
            }
        };
        count(0, 0);
        count(1, 3);
        const bool has5 = lt < 64;
        if (has5) count(5, 6);
        put(0, 0);
        put(1, 3);
        if (has5) put(5, 6);
        if (((pv[2].x ^ tg) | (pv[3].x ^ tg) | (pv[4].x ^ tg)) >> 8) {
#pragma unroll
            for (int m = 2; m < 5; m++) if (cnt > 6 * m) pv[m] = fetch(px0 + m * (2 * NCTA));
        }
#pragma unroll
        for (int m = 2; m < 5; m++) {
            if (__any_sync(0xffffffffu, cnt > 6 * m)) { count(m, 0); put(m, 0); }
        }
        TRACE(28);
        lt_bar();
        if (lt < 96) {
            const uint32_t deg = (lt < NPC) ? lds32(sb + SM_KEYS + lt * 4) : 0;
            const uint32_t bin = 63 - min(deg, 63u);
            const uint32_t r0 = atoms_add_p(lt < NPC, sb + SM_DBIN + bin * 4, 1);
            if (deg > NCAP) sts32(sb + SM_FLAG, 1);
            asm volatile("bar.sync 5, 96;" ::: "memory");
            const uint2 c2 = lds64(sb + SM_DBIN + lane * 8);
            uint32_t inc = c2.x + c2.y;
#pragma unroll
            for (int o = 1; o < 32; o <<= 1) { const uint32_t u = __shfl_up_sync(0xffffffffu, inc, o); if (lane >= o) inc += u; }
            const uint32_t ex = inc - c2.x - c2.y;
            const uint32_t pe = __shfl_sync(0xffffffffu, ex, bin >> 1), p0 = __shfl_sync(0xffffffffu, c2.x, bin >> 1);
            const int rank = pe + ((bin & 1) ? p0 : 0) + r0;
            const int k = rank >> 4, pos = rank & 15;
            const int tile = (k == 4) ? 11 - pos : ((pos < 4) ? 12 + ((k & 1) ? 3 - pos : pos) : ((k < 3) ? pos - 4 : 15 - pos));
            if (lt < NPC) {
                sts32(sb + SM_TDEG + (tile * 8 + k) * 4, deg);
                sts8(sb + SM_TNODE + tile * 8 + k, lt);
            }
        }
        TRACE(29);
        TRACE(30);
    }
    TRACE(31);
    __syncthreads();
    TRACE(32);
    bool slow = lds32(sb + SM_FLAG) != 0;

    constexpr uint32_t RD = SM_R1 - SM_R0;
    const uint32_t ring0 = sb + SM_R0 + w * STAGE;
    const char* tab_l = p.table + lane * 16;
    asm volatile("" : "+l"(tab_l));
    const char* e_l = (const char*)p.e_attr + (mi & 1) * 16;
    asm volatile("" : "+l"(e_l));
    const uint32_t cpo = lane * 16;
    const uint32_t elo = 4096 + rr * 32 + (((mi & 1) ^ ((rr >> 2) & 1)) << 4);
    const uint32_t lsrc = sb + SM_LSE + w * TCAP * 4, lid = sb + SM_LID + w * TCAP;
    const uint32_t lec = rr * 4;

    auto issue_full = [&](uint32_t lp, uint32_t dl) {
        const uint4 s0 = lds128(lp), s1 = lds128(lp + 16);
        const uint32_t eo = lds32(lp + lec);
        const uint32_t sv[8] = {s0.x, s0.y, s0.z, s0.w, s1.x, s1.y, s1.z, s1.w};
#pragma unroll
        for (int j = 0; j < 8; j++) cp16(ring0 + dl + (cpo ^ (j << 4)) + j * 512, madw(sv[j] & 0x3FFF, 512, tab_l));
        cp16(ring0 + dl + elo, madw(eo >> 14, 32, e_l));
    };
    auto issue0 = [&]() {
        const int cnt = lds32(sb + SM_TCNT + w * 4), nit = (cnt + 7) >> 3;
        if (nit > 0) {
            const int pad = nit * 8 - cnt;
            const uint4 s0 = lds128(lsrc), s1 = lds128(lsrc + 16);
            const uint32_t eo = lds32(lsrc + lec);
            const uint32_t sv[8] = {s0.x, s0.y, s0.z, s0.w, s1.x, s1.y, s1.z, s1.w};
#pragma unroll
            for (int j = 0; j < 8; j++) cp16z(ring0 + (cpo ^ (j << 4)) + j * 512, madw(sv[j] & 0x3FFF, 512, tab_l), (j >= pad) ? 16 : 0);
            cp16z(ring0 + elo, madw(eo >> 14, 32, e_l), (rr >= pad) ? 16 : 0);
        }
        cp_commit();
    };
    auto issue1 = [&]() {
        if ((int)lds32(sb + SM_TCNT + w * 4) > 8) issue_full(lsrc + 32, RD);
        cp_commit();
    };
    uint32_t bar_v = 0;
    bool over = false;
    if (tid == 0) asm volatile("ld.relaxed.gpu.global.u32 %0, [%1];" : "=r"(bar_v) : "l"(p.bar) : "memory");
    if (!slow) {
        const uint2 tn = lds64(sb + SM_TNODE + w * 8);
        const uint4 dg = lds128(sb + SM_TDEG + w * 32);
        const uint32_t p1 = dg.x, p2 = p1 + dg.y, p3 = p2 + dg.z, p4 = p3 + dg.w, tot = p4 + lds32(sb + SM_TDEG + w * 32 + 16);
        const uint32_t pad = (0u - tot) & 7u;
        if (lane == 0) sts32(sb + SM_TCNT + w * 4, tot);
        over = tot + pad > TCAP;
        uint32_t wd[TCAP / 32], sl[TCAP / 32];
#pragma unroll
        for (int r = 0; r < TCAP / 32; r++) {
            const uint32_t q = lane + 32 * r - pad;
            sl[r] = (q >= p1) + (q >= p2) + (q >= p3) + (q >= p4);
            const uint32_t pre = (q >= p4) ? p4 : ((q >= p3) ? p3 : ((q >= p2) ? p2 : ((q >= p1) ? p1 : 0)));
            const uint32_t node = prmt(tn.x, tn.y, sl[r]) & 0xFF;
            wd[r] = lds32(sb + SM_NL + ((q < tot) ? (node * NCAP + q - pre) * 4 : 0));
        }
#pragma unroll
        for (int r = 0; r < TCAP / 32; r++) {
            const uint32_t q = lane + 32 * r - pad;
            sts32(lsrc + (lane + 32 * r) * 4, (q < tot) ? wd[r] : 0);
            sts8(lid + lane + 32 * r, (q < tot) ? sl[r] * 16 : 0x7F);
        }
    }
    TRACE(10);
    if (tid == 0) {
        int it = 0;
        while ((int)(bar_v - bar_target) < 0 && ++it < SPIN_LIMIT)
            asm volatile("ld.relaxed.gpu.global.u32 %0, [%1];" : "=r"(bar_v) : "l"(p.bar) : "memory");
    }
    slow = __syncthreads_or(slow || over);
    TRACE(11);
    if (!slow) {
        issue0();
        issue1();
    } else {
        if (tid < NPC) sts8(sb + SM_TNODE + (tid & 15) * 8 + (tid >> 4), tid);
        __syncthreads();
    }
    TRACE(33);
    load_node_frags();
    TRACE(34);

    const uint32_t ldo = rr * 512 + ((mi ^ rr) << 4);
    const uint32_t sel = (g | ((8 | g) << 4) | (g << 8) | ((8 | g) << 12)) |
                         (((2 * t) | ((8 | (2 * t)) << 4) | ((2 * t + 1) << 8) | ((8 | (2 * t + 1)) << 12)) << 16);
    const uint32_t gg = (g * 16) | ((g * 16) << 16);
    const uint32_t tt = (t * 32) | ((t * 32 + 16) << 16);

    auto compute = [&](uint32_t st, uint32_t idp) {
        uint32_t eb[2];
        ldsm2(eb, st + elo);
        const uint2 iw = lds64(idp);
        const uint32_t sx = seteq_bf16x2(prmt(iw.x, iw.y, sel), tt);
        const uint32_t sa = seteq_bf16x2(prmt(iw.x, iw.y, sel >> 16), gg);
#pragma unroll
        for (int jj = 0; jj < 4; jj++) {
            uint32_t xb[4], hv[4];
            const uint32_t la = st + (ldo ^ ((jj & 1) << 6)) + (jj >> 1) * 128;
            ldsm4(xb, la);
            ldsm4t(hv, la + 256);
#pragma unroll
            for (int u = 0; u < 2; u++) {
                const int j = 2 * jj + u;
                float d[4];
                mma16816_z(d, Cf[j][0], Cf[j][1], Cf[j][2], Cf[j][3], eb[0], eb[1]);
                mma1688(d, xAf[j][0], xAf[j][1], sx);
                mma16816(d, ident, 0u, 0u, ident, xb[2 * u], xb[2 * u + 1]);
                const uint32_t m0 = fma_bf16x2(pack_bf16(tanh_ap(d[0]), tanh_ap(d[1])), hv[2 * u], hv[2 * u]);
                const uint32_t m1 = fma_bf16x2(pack_bf16(tanh_ap(d[2]), tanh_ap(d[3])), hv[2 * u + 1], hv[2 * u + 1]);
                mma1688(agg[j], m0, m1, sa);
            }
        }
    };

    const int nseg = slow ? NSEG : 1;
#pragma unroll 1
    for (int seg = 0; seg < nseg; seg++) {
        if (slow) {
            __syncthreads();
            if (tid < 16) sts32(sb + SM_TCNT + tid * 4, 0);
            __syncthreads();
            const int e = seg * TCAP + tid;
            int loc = -1; uint32_t r = 0;
            if (tid < TCAP && e < EE) {
                const int dd = __ldg(p.dst + e) - b * NPC;
                if (dd >= 0 && dd < NPC) { loc = dd; r = atoms_add(sb + SM_TCNT + (loc & 15) * 4, 1); }
            }
            __syncthreads();
            if (loc >= 0) {
                const uint32_t tile = loc & 15, tot = lds32(sb + SM_TCNT + tile * 4);
                const uint32_t pos = tile * TCAP + ((0u - tot) & 7u) + r;
                sts32(sb + SM_LSE + pos * 4, (uint32_t)__ldg(p.src + e) | ((uint32_t)e << 14));
                sts8(sb + SM_LID + pos, (loc >> 4) << 4);
            }
            const int pad = (0 - (int)lds32(sb + SM_TCNT + w * 4)) & 7;
            if (lane < pad) { sts8(sb + SM_LID + w * TCAP + lane, 0x7F); sts32(sb + SM_LSE + (w * TCAP + lane) * 4, 0); }
            __syncthreads();
            issue0();
            issue1();
        }
        const int nit = __shfl_sync(0xffffffffu, ((int)lds32(sb + SM_TCNT + w * 4) + 7) >> 3, 0);
        uint32_t st = ring0, so = ring0 + RD, lp = lsrc + 32, idp = lid;
        const uint32_t lend = lsrc + nit * 32;
        constexpr int AVG_NIT = (EE + NCTA * 128 - 1) / (NCTA * 128);
        constexpr int HEAVY = EE / NN * NPC * 207 / 200;
        const int ctot = __reduce_add_sync(0xffffffffu, (lane < 16) ? (int)lds32(sb + SM_TCNT + lane * 4) : 0);
        if (nit <= AVG_NIT && ctot <= HEAVY) {
#pragma unroll 1
            for (; lp <= lend; lp += 32, idp += 8) {
                if (idp == lid) cp_wait<1>(); else cp_wait<0>();
                __syncwarp();
                if (idp != lid && lp < lend) issue_full(lp, so - ring0);
                cp_commit();
                compute(st, idp);
                const uint32_t tmp = st; st = so; so = tmp;
            }
        } else {
#pragma unroll 1
            for (; lp <= lend; lp += 32, idp += 8) {
                cp_wait<1>();
                __syncwarp();
                compute(st, idp);
                __syncwarp();
                if (lp + 32 < lend) issue_full(lp + 32, st - ring0);
                cp_commit();
                const uint32_t tmp = st; st = so; so = tmp;
            }
        }
        cp_wait<0>();
        __syncwarp();
    }
    TRACE(35);

    {
        uint32_t o[8][2];
#pragma unroll
        for (int j = 0; j < 8; j++) {
            float v[4];
#pragma unroll
            for (int q = 0; q < 4; q++) { const float h = agg[j][q]; v[q] = fmaf(h, tanh_ap(h), h); }
            o[j][0] = pack_bf16(v[0], v[1]); o[j][1] = pack_bf16(v[2], v[3]);
        }
#pragma unroll
        for (int jp = 0; jp < 4; jp++) {
            const int c = 4 * jp + mi;
            stsm4t(ring0 + rr * 256 + ((c & 8) << 4) + (((c & 7) ^ rr) << 4), o[2 * jp][0], o[2 * jp][1], o[2 * jp + 1][0], o[2 * jp + 1][1]);
        }
        __syncwarp();
#pragma unroll
        for (int i = 0; i < 3; i++) {
            const int idx = lane + 32 * i, row = idx >> 4, c = idx & 15;
            const int nd = b * NPC + (int)lds8(sb + SM_TNODE + w * 8 + (row & 7));
            if (row < nslot && nd < NN) {
                const uint4 v = lds128(ring0 + row * 256 + ((c & 8) << 4) + (((c & 7) ^ row) << 4));
                *(uint4*)((char*)p.out + (size_t)nd * 256 + c * 16) = v;
            }
        }
    }
    TRACE(36);
}

__device__ __align__(16) bf16 g_fb_xa[NN * 128];
__device__ __align__(16) float g_fb_h[NN * 128];

__global__ void fb_node_kernel(const bf16* x, const bf16* uw, const bf16* vw, const bf16* gw, bf16* table) {
    __shared__ float xs[128];
    const int n = blockIdx.x, f = threadIdx.x;
    xs[f] = __bfloat162float(x[n * 128 + f]);
    __syncthreads();
    float a = 0.f, bb = 0.f, v = 0.f, u = 0.f;
    for (int k = 0; k < 128; k++) {
        const float xv = xs[k];
        a += xv * __bfloat162float(gw[k * 128 + f]);
        bb += xv * __bfloat162float(gw[(128 + k) * 128 + f]);
        v += xv * __bfloat162float(vw[k * 128 + f]);
        u += xv * __bfloat162float(uw[k * 128 + f]);
    }
    table[n * 256 + f] = __float2bfloat16(0.5f * bb);
    table[n * 256 + 128 + f] = __float2bfloat16(0.25f * v);
    g_fb_xa[n * 128 + f] = __float2bfloat16(0.5f * a);
    g_fb_h[n * 128 + f] = 0.5f * u;
}
__global__ void fb_edge_kernel(const bf16* e_attr, const int* src, const int* dst, const bf16* gw, const bf16* table) {
    const int e = blockIdx.x, f = threadIdx.x, s = src[e], d = dst[e];
    float z = 0.f;
    for (int k = 0; k < 16; k++) z += __bfloat162float(e_attr[e * 16 + k]) * __bfloat162float(gw[(256 + k) * 128 + f]);
    z = 0.5f * z + __bfloat162float(g_fb_xa[d * 128 + f]) + __bfloat162float(table[s * 256 + f]);
    const float hv = __bfloat162float(table[s * 256 + 128 + f]);
    atomicAdd(&g_fb_h[d * 128 + f], fmaf(hv, tanhf(z), hv));
}
__global__ void fb_out_kernel(bf16* out) {
    const int i = blockIdx.x * 128 + threadIdx.x;
    const float h = g_fb_h[i];
    out[i] = __float2bfloat16(fmaf(h, tanhf(h), h));
}

typedef CUresult (*EncodeFn)(CUtensorMap*, CUtensorMapDataType, cuuint32_t, void*, const cuuint64_t*, const cuuint64_t*,
                             const cuuint32_t*, const cuuint32_t*, CUtensorMapInterleave, CUtensorMapSwizzle,
                             CUtensorMapL2promotion, CUtensorMapFloatOOBfill);

static void make_map(EncodeFn enc, CUtensorMap* tm, const void* base, int rows, int cols, int box_rows) {
    cuuint64_t dims[2] = {(cuuint64_t)cols, (cuuint64_t)rows};
    cuuint64_t strides[1] = {(cuuint64_t)cols * 2};
    cuuint32_t box[2] = {64, (cuuint32_t)box_rows};
    cuuint32_t es[2] = {1, 1};
    enc(tm, CU_TENSOR_MAP_DATA_TYPE_BFLOAT16, 2, (void*)base, dims, strides, box, es, CU_TENSOR_MAP_INTERLEAVE_NONE,
        CU_TENSOR_MAP_SWIZZLE_128B, CU_TENSOR_MAP_L2_PROMOTION_NONE, CU_TENSOR_MAP_FLOAT_OOB_FILL_NONE);
}

}

extern "C" void kernel_launch(void* const* d_in, const int* in_sizes, int n_in, void* d_out, int out_size) {
    using namespace egc;
    (void)in_sizes; (void)n_in; (void)out_size;
    static EncodeFn enc = nullptr;
    static void* table = nullptr;
    static void* xch = nullptr;
    static void* bar = nullptr;
    static bool persistent = false;
    if (!enc) {
        void* fn = nullptr;
        cudaDriverEntryPointQueryResult qr;
        cudaGetDriverEntryPoint("cuTensorMapEncodeTiled", &fn, cudaEnableDefault, &qr);
        enc = (EncodeFn)fn;
        cudaGetSymbolAddress(&table, g_table);
        cudaGetSymbolAddress(&xch, g_xch);
        cudaGetSymbolAddress(&bar, g_bar);
        cudaFuncSetAttribute(egc_kernel, cudaFuncAttributeMaxDynamicSharedMemorySize, SMEM_BYTES);
        int dev = 0, sms = 0, per_sm = 0;
        cudaGetDevice(&dev);
        cudaDeviceGetAttribute(&sms, cudaDevAttrMultiProcessorCount, dev);
        cudaOccupancyMaxActiveBlocksPerMultiprocessor(&per_sm, egc_kernel, NTHR, SMEM_BYTES);
        persistent = enc != nullptr && sms * per_sm >= NCTA;
    }
    if (!persistent) {
        const bf16* x = (const bf16*)d_in[0];
        fb_node_kernel<<<NN, 128, 0, cudaStreamPerThread>>>(x, (const bf16*)d_in[4], (const bf16*)d_in[5], (const bf16*)d_in[6], (bf16*)table);
        fb_edge_kernel<<<EE, 128, 0, cudaStreamPerThread>>>((const bf16*)d_in[1], (const int*)d_in[2], (const int*)d_in[3], (const bf16*)d_in[6], (const bf16*)table);
        fb_out_kernel<<<NN, 128, 0, cudaStreamPerThread>>>((bf16*)d_out);
        return;
    }
    CUtensorMap tm_x, tm_g, tm_u, tm_v, tm_t;
    make_map(enc, &tm_x, d_in[0], NN, 128, 80);
    make_map(enc, &tm_u, d_in[4], 128, 128, 128);
    make_map(enc, &tm_v, d_in[5], 128, 128, 128);
    make_map(enc, &tm_g, d_in[6], 272, 128, 128);
    make_map(enc, &tm_t, table, NN, 256, NPC);
    Params p;
    p.e_attr = (const bf16*)d_in[1];
    p.src = (const int*)d_in[2];
    p.dst = (const int*)d_in[3];
    p.gw = (const bf16*)d_in[6];
    p.out = (bf16*)d_out;
    p.bar = (unsigned*)bar;
    p.xch = (uint4*)xch;
    p.table = (const char*)table;
    egc_kernel<<<NCTA, NTHR, SMEM_BYTES, cudaStreamPerThread>>>(p, tm_x, tm_g, tm_u, tm_v, tm_t);
}
```

```cpp
#include <cuda_runtime.h>
#include <cuda_bf16.h>
#include <cuda.h>
#include <stdint.h>
#include <type_traits>

namespace egc {

typedef __nv_bfloat16 bf16;

constexpr int NN = 10000, EE = 160000;
constexpr int NCTA = 132, NPC = 76, ECH = 1216, NTHR = 512;
constexpr int PIECES = 10, XCAP = 3 * PIECES;
constexpr int TCAP = 96;
constexpr int NSEG = (EE + TCAP - 1) / TCAP;
constexpr int SPIN_LIMIT = 1 << 20;
constexpr uint32_t START_DELAY = 420;

constexpr int STAGE = 4352;
constexpr int SM_R0 = 0;
constexpr int SM_R1 = 16 * STAGE;
constexpr int SM_S = SM_R1;
constexpr int SM_WU = SM_R1 + 8 * STAGE;
constexpr int SM_WA = SM_R1 + 16 * STAGE;
constexpr int SM_X = SM_WA + 32768;
constexpr int SM_C = SM_X + 20480;
constexpr int SM_LSE = SM_C + 4096;
constexpr int SM_LID = SM_LSE + 6144 + 128;
constexpr int SM_HIST = SM_LID + 1536 + 32;
constexpr int SM_KEYS = SM_HIST + 544;
constexpr int SM_CURS = SM_KEYS + 512;
constexpr int SM_DBIN = SM_CURS + 512;
constexpr int SM_TDEG = SM_DBIN + 256;
constexpr int SM_TNODE = SM_TDEG + 512;
constexpr int SM_TCNT = SM_TNODE + 128;
constexpr int SM_FLAG = SM_TCNT + 64;
constexpr int NCAP = 40;
constexpr int SM_NL = SM_FLAG + 16;
constexpr int SM_BAR = SM_NL + NPC * NCAP * 4 + 128;
constexpr int SM_TRACE = SM_BAR + 9 * 8 + 8;
constexpr int SM_END = SM_TRACE + 2 * 48 * 4;
constexpr int SMEM_BYTES = SM_END + 1024;

__device__ __align__(1024) uint4 g_table[NN * 32];
__device__ __align__(1024) uint4 g_xch[NCTA * NCTA * PIECES];
__device__ __align__(128) unsigned g_bar[32];
#define TRACE(i) do {} while (0)

__device__ __forceinline__ void mma16816(float* d, uint32_t a0, uint32_t a1, uint32_t a2, uint32_t a3, uint32_t b0, uint32_t b1) {
    asm("mma.sync.aligned.m16n8k16.row.col.f32.bf16.bf16.f32 {%0,%1,%2,%3}, {%4,%5,%6,%7}, {%8,%9}, {%0,%1,%2,%3};"
        : "+f"(d[0]), "+f"(d[1]), "+f"(d[2]), "+f"(d[3]) : "r"(a0), "r"(a1), "r"(a2), "r"(a3), "r"(b0), "r"(b1));
}
__device__ __forceinline__ void mma16816_z(float* d, uint32_t a0, uint32_t a1, uint32_t a2, uint32_t a3, uint32_t b0, uint32_t b1) {
    asm("mma.sync.aligned.m16n8k16.row.col.f32.bf16.bf16.f32 {%0,%1,%2,%3}, {%4,%5,%6,%7}, {%8,%9}, {%10,%10,%10,%10};"
        : "=f"(d[0]), "=f"(d[1]), "=f"(d[2]), "=f"(d[3]) : "r"(a0), "r"(a1), "r"(a2), "r"(a3), "r"(b0), "r"(b1), "f"(0.f));
}
__device__ __forceinline__ void mma1688(float* d, uint32_t a0, uint32_t a1, uint32_t b0) {
    asm("mma.sync.aligned.m16n8k8.row.col.f32.bf16.bf16.f32 {%0,%1,%2,%3}, {%4,%5}, {%6}, {%0,%1,%2,%3};"
        : "+f"(d[0]), "+f"(d[1]), "+f"(d[2]), "+f"(d[3]) : "r"(a0), "r"(a1), "r"(b0));
}
__device__ __forceinline__ void mma1688_z(float* d, uint32_t a0, uint32_t a1, uint32_t b0) {
    asm("mma.sync.aligned.m16n8k8.row.col.f32.bf16.bf16.f32 {%0,%1,%2,%3}, {%4,%5}, {%6}, {%7,%7,%7,%7};"
        : "=f"(d[0]), "=f"(d[1]), "=f"(d[2]), "=f"(d[3]) : "r"(a0), "r"(a1), "r"(b0), "f"(0.f));
}
__device__ __forceinline__ void ldsm4(uint32_t* r, uint32_t addr) {
    asm volatile("ldmatrix.sync.aligned.m8n8.x4.shared.b16 {%0,%1,%2,%3}, [%4];" : "=r"(r[0]), "=r"(r[1]), "=r"(r[2]), "=r"(r[3]) : "r"(addr) : "memory");
}
__device__ __forceinline__ void ldsm4t(uint32_t* r, uint32_t addr) {
    asm volatile("ldmatrix.sync.aligned.m8n8.x4.trans.shared.b16 {%0,%1,%2,%3}, [%4];" : "=r"(r[0]), "=r"(r[1]), "=r"(r[2]), "=r"(r[3]) : "r"(addr) : "memory");
}
__device__ __forceinline__ void ldsm2(uint32_t* r, uint32_t addr) {
    asm volatile("ldmatrix.sync.aligned.m8n8.x2.shared.b16 {%0,%1}, [%2];" : "=r"(r[0]), "=r"(r[1]) : "r"(addr) : "memory");
}
__device__ __forceinline__ void stsm4t(uint32_t addr, uint32_t r0, uint32_t r1, uint32_t r2, uint32_t r3) {
    asm volatile("stmatrix.sync.aligned.m8n8.x4.trans.shared.b16 [%0], {%1,%2,%3,%4};" :: "r"(addr), "r"(r0), "r"(r1), "r"(r2), "r"(r3) : "memory");
}
__device__ __forceinline__ float tanh_ap(float x) { float r; asm("tanh.approx.f32 %0, %1;" : "=f"(r) : "f"(x)); return r; }
__device__ __forceinline__ uint32_t pack_bf16(float lo, float hi) { uint32_t r; asm("cvt.rn.bf16x2.f32 %0, %1, %2;" : "=r"(r) : "f"(hi), "f"(lo)); return r; }
__device__ __forceinline__ uint32_t fma_bf16x2(uint32_t a, uint32_t b, uint32_t c) { uint32_t r; asm("fma.rn.bf16x2 %0, %1, %2, %3;" : "=r"(r) : "r"(a), "r"(b), "r"(c)); return r; }
__device__ __forceinline__ uint32_t mul_bf16x2(uint32_t a, uint32_t b) { uint32_t r; asm("mul.rn.bf16x2 %0, %1, %2;" : "=r"(r) : "r"(a), "r"(b)); return r; }
__device__ __forceinline__ uint32_t seteq_bf16x2(uint32_t a, uint32_t b) { uint32_t r; asm("set.eq.bf16x2.bf16x2 %0, %1, %2;" : "=r"(r) : "r"(a), "r"(b)); return r; }
__device__ __forceinline__ uint32_t prmt(uint32_t a, uint32_t b, uint32_t s) { uint32_t r; asm("prmt.b32 %0, %1, %2, %3;" : "=r"(r) : "r"(a), "r"(b), "r"(s)); return r; }
__device__ __forceinline__ uint32_t shl_clamp(uint32_t a, uint32_t s) { uint32_t r; asm("shl.b32 %0, %1, %2;" : "=r"(r) : "r"(a), "r"(s)); return r; }
__device__ __forceinline__ void cp16(uint32_t dst, const void* src) { asm volatile("cp.async.cg.shared.global [%0], [%1], 16;" :: "r"(dst), "l"(src) : "memory"); }
__device__ __forceinline__ void cp16z(uint32_t dst, const void* src, uint32_t sz) { asm volatile("cp.async.cg.shared.global [%0], [%1], 16, %2;" :: "r"(dst), "l"(src), "r"(sz) : "memory"); }
__device__ __forceinline__ const void* madw(uint32_t a, uint32_t m, const void* base) {
    const void* r; asm("mad.wide.u32 %0, %1, %2, %3;" : "=l"(r) : "r"(a), "r"(m), "l"(base)); return r;
}
__device__ __forceinline__ void cp16_p(bool p, uint32_t dst, const void* src) {
    asm volatile("{\n.reg .pred p;\nsetp.ne.u32 p, %2, 0;\n@p cp.async.cg.shared.global [%0], [%1], 16;\n}" :: "r"(dst), "l"(src), "r"((uint32_t)p) : "memory");
}
__device__ __forceinline__ void cp_commit() { asm volatile("cp.async.commit_group;" ::: "memory"); }
template <int N> __device__ __forceinline__ void cp_wait() { asm volatile("cp.async.wait_group %0;" :: "n"(N) : "memory"); }
__device__ __forceinline__ uint4 lds128(uint32_t a) { uint4 v; asm volatile("ld.shared.v4.u32 {%0,%1,%2,%3}, [%4];" : "=r"(v.x), "=r"(v.y), "=r"(v.z), "=r"(v.w) : "r"(a) : "memory"); return v; }
__device__ __forceinline__ uint2 lds64(uint32_t a) { uint2 v; asm volatile("ld.shared.v2.u32 {%0,%1}, [%2];" : "=r"(v.x), "=r"(v.y) : "r"(a) : "memory"); return v; }
__device__ __forceinline__ uint32_t lds32(uint32_t a) { uint32_t v; asm volatile("ld.shared.u32 %0, [%1];" : "=r"(v) : "r"(a) : "memory"); return v; }
__device__ __forceinline__ uint32_t lds8(uint32_t a) { uint32_t v; asm volatile("ld.shared.u8 %0, [%1];" : "=r"(v) : "r"(a) : "memory"); return v; }
__device__ __forceinline__ void sts32(uint32_t a, uint32_t v) { asm volatile("st.shared.u32 [%0], %1;" :: "r"(a), "r"(v) : "memory"); }
__device__ __forceinline__ void sts8(uint32_t a, uint32_t v) { asm volatile("st.shared.u8 [%0], %1;" :: "r"(a), "r"(v) : "memory"); }
__device__ __forceinline__ void sts128(uint32_t a, uint4 v) { asm volatile("st.shared.v4.u32 [%0], {%1,%2,%3,%4};" :: "r"(a), "r"(v.x), "r"(v.y), "r"(v.z), "r"(v.w) : "memory"); }
__device__ __forceinline__ uint32_t atoms_add(uint32_t a, uint32_t v) { uint32_t r; asm volatile("atom.shared.add.u32 %0, [%1], %2;" : "=r"(r) : "r"(a), "r"(v) : "memory"); return r; }
__device__ __forceinline__ void reds_add(uint32_t a, uint32_t v) { asm volatile("red.shared.add.u32 [%0], %1;" :: "r"(a), "r"(v) : "memory"); }
__device__ __forceinline__ uint32_t atoms_add_p(bool p, uint32_t a, uint32_t v) {
    uint32_t r = 0;
    asm volatile("{\n.reg .pred p;\nsetp.ne.u32 p, %3, 0;\n@p atom.shared.add.u32 %0, [%1], %2;\n}" : "+r"(r) : "r"(a), "r"(v), "r"((uint32_t)p) : "memory");
    return r;
}
__device__ __forceinline__ uint32_t lds32_p(bool p, uint32_t a) {
    uint32_t r = 0;
    asm volatile("{\n.reg .pred p;\nsetp.ne.u32 p, %2, 0;\n@p ld.shared.u32 %0, [%1];\n}" : "+r"(r) : "r"(a), "r"((uint32_t)p) : "memory");
    return r;
}
__device__ __forceinline__ void sts32_p(bool p, uint32_t a, uint32_t v) {
    asm volatile("{\n.reg .pred p;\nsetp.ne.u32 p, %2, 0;\n@p st.shared.u32 [%0], %1;\n}" :: "r"(a), "r"(v), "r"((uint32_t)p) : "memory");
}
__device__ __forceinline__ void sts8_p(bool p, uint32_t a, uint32_t v) {
    asm volatile("{\n.reg .pred p;\nsetp.ne.u32 p, %2, 0;\n@p st.shared.u8 [%0], %1;\n}" :: "r"(a), "r"(v), "r"((uint32_t)p) : "memory");
}
__device__ __forceinline__ void st_piece(uint4* p, uint4 v) {
    asm volatile("{\n.reg .b128 q;\n.reg .b64 lo, hi;\nmov.b64 lo, {%1,%2};\nmov.b64 hi, {%3,%4};\nmov.b128 q, {lo, hi};\nst.relaxed.gpu.global.b128 [%0], q;\n}"
                 :: "l"(p), "r"(v.x), "r"(v.y), "r"(v.z), "r"(v.w) : "memory");
}
__device__ __forceinline__ uint4 ld_piece(const uint4* p) {
    uint4 v;
    asm volatile("{\n.reg .b128 q;\n.reg .b64 lo, hi;\nld.relaxed.gpu.global.b128 q, [%4];\nmov.b128 {lo, hi}, q;\nmov.b64 {%0,%1}, lo;\nmov.b64 {%2,%3}, hi;\n}"
                 : "=r"(v.x), "=r"(v.y), "=r"(v.z), "=r"(v.w) : "l"(p) : "memory");
    return v;
}
__device__ __forceinline__ void mbar_init(uint32_t bar, uint32_t cnt) { asm volatile("mbarrier.init.shared::cta.b64 [%0], %1;" :: "r"(bar), "r"(cnt) : "memory"); }
__device__ __forceinline__ void mbar_expect(uint32_t bar, uint32_t bytes) { asm volatile("mbarrier.arrive.expect_tx.shared::cta.b64 _, [%0], %1;" :: "r"(bar), "r"(bytes) : "memory"); }
__device__ __forceinline__ void mbar_wait(uint32_t bar, uint32_t parity) {
    uint32_t ok; int it = 0;
    do {
        asm volatile("{\n.reg .pred p;\nmbarrier.try_wait.parity.shared::cta.b64 p, [%1], %2;\nselp.u32 %0, 1, 0, p;\n}" : "=r"(ok) : "r"(bar), "r"(parity) : "memory");
    } while (!ok && ++it < (1 << 22));
}
__device__ __forceinline__ void tma_load2d(uint32_t dst, const CUtensorMap* tm, int c0, int c1, uint32_t bar) {
    asm volatile("cp.async.bulk.tensor.2d.shared::cluster.global.mbarrier::complete_tx::bytes [%0], [%1, {%3, %4}], [%2];"
                 :: "r"(dst), "l"(tm), "r"(bar), "r"(c0), "r"(c1) : "memory");
}
__device__ __forceinline__ void tma_load2d_mc(uint32_t dst, const CUtensorMap* tm, int c0, int c1, uint32_t bar) {
    asm volatile("cp.async.bulk.tensor.2d.shared::cluster.global.mbarrier::complete_tx::bytes.multicast::cluster [%0], [%1, {%3, %4}], [%2], %5;"
                 :: "r"(dst), "l"(tm), "r"(bar), "r"(c0), "r"(c1), "h"((uint16_t)3) : "memory");
}
__device__ __forceinline__ void tma_store2d(const CUtensorMap* tm, int c0, int c1, uint32_t src) {
    asm volatile("cp.async.bulk.tensor.2d.global.shared::cta.bulk_group [%0, {%2, %3}], [%1];"
                 :: "l"(tm), "r"(src), "r"(c0), "r"(c1) : "memory");
}
__device__ __forceinline__ void spin(uint32_t cycles) {
    uint32_t c0, c1;
    asm volatile("mov.u32 %0, %%clock;" : "=r"(c0));
    do { asm volatile("mov.u32 %0, %%clock;" : "=r"(c1)); } while (c1 - c0 < cycles);
}
__device__ __forceinline__ void lt_bar() { asm volatile("bar.sync 3, 256;" ::: "memory"); }
__device__ __forceinline__ void wg_bar(int id) { asm volatile("bar.sync %0, 128;" :: "r"(id) : "memory"); }

__device__ __forceinline__ void wgmma_n80(float (&d)[40], uint64_t da, uint64_t db, int acc) {
    asm volatile("{\n.reg .pred p;\nsetp.ne.b32 p, %42, 0;\n"
        "wgmma.mma_async.sync.aligned.m64n80k16.f32.bf16.bf16 "
        "{%0,%1,%2,%3,%4,%5,%6,%7,%8,%9,%10,%11,%12,%13,%14,%15,%16,%17,%18,%19,"
        "%20,%21,%22,%23,%24,%25,%26,%27,%28,%29,%30,%31,%32,%33,%34,%35,%36,%37,%38,%39}, "
        "%40, %41, p, 1, 1, 1, 0;\n}\n"
        : "+f"(d[0]), "+f"(d[1]), "+f"(d[2]), "+f"(d[3]), "+f"(d[4]), "+f"(d[5]), "+f"(d[6]), "+f"(d[7]), "+f"(d[8]), "+f"(d[9]),
          "+f"(d[10]), "+f"(d[11]), "+f"(d[12]), "+f"(d[13]), "+f"(d[14]), "+f"(d[15]), "+f"(d[16]), "+f"(d[17]), "+f"(d[18]), "+f"(d[19]),
          "+f"(d[20]), "+f"(d[21]), "+f"(d[22]), "+f"(d[23]), "+f"(d[24]), "+f"(d[25]), "+f"(d[26]), "+f"(d[27]), "+f"(d[28]), "+f"(d[29]),
          "+f"(d[30]), "+f"(d[31]), "+f"(d[32]), "+f"(d[33]), "+f"(d[34]), "+f"(d[35]), "+f"(d[36]), "+f"(d[37]), "+f"(d[38]), "+f"(d[39])
        : "l"(da), "l"(db), "r"(acc));
}

__device__ __forceinline__ void gemm_issue(float (&d)[40], uint32_t wbase, uint32_t xbase) {
    asm volatile("wgmma.fence.sync.aligned;" ::: "memory");
#pragma unroll
    for (int s = 0; s < 8; s++) {
        const uint32_t aa = wbase + s * 2048, ab = xbase + (s >> 2) * 10240 + (s & 3) * 32;
        const uint64_t da = (uint64_t)((aa & 0x3FFFF) >> 4) | ((uint64_t)64 << 16) | ((uint64_t)64 << 32) | ((uint64_t)1 << 62);
        const uint64_t db = (uint64_t)((ab & 0x3FFFF) >> 4) | ((uint64_t)1 << 16) | ((uint64_t)64 << 32) | ((uint64_t)1 << 62);
        wgmma_n80(d, da, db, s > 0);
    }
    asm volatile("wgmma.commit_group.sync.aligned;" ::: "memory");
}
__device__ __forceinline__ void gemm_wait(float (&d)[40]) {
    asm volatile("wgmma.wait_group.sync.aligned 0;" ::: "memory");
#pragma unroll
    for (int i = 0; i < 40; i++) asm volatile("" : "+f"(d[i]) :: "memory");
}
__device__ __forceinline__ void gemm_store(const float (&d)[40], float sc, uint32_t base, int w4, int lane) {
    const int mi = lane >> 3, rr = lane & 7;
    const uint32_t sa = base + (rr + 8 * (mi >> 1)) * 128 + (((2 * w4 + (mi & 1)) ^ rr) << 4);
#pragma unroll
    for (int p = 0; p < 5; p++) {
        const float* q = d + 8 * p;
        stsm4t(sa + p * 2048, pack_bf16(q[0] * sc, q[1] * sc), pack_bf16(q[2] * sc, q[3] * sc),
               pack_bf16(q[4] * sc, q[5] * sc), pack_bf16(q[6] * sc, q[7] * sc));
    }
}

struct Params {
    const int* dst;
    const int* src;
    unsigned* bar;
    uint4* xch;
    const bf16* gw;
    const bf16* e_attr;
    const char* table;
    bf16* out;
};

__global__ void __launch_bounds__(NTHR, 1)
egc_kernel(const Params p, const __grid_constant__ CUtensorMap tm_x, const __grid_constant__ CUtensorMap tm_g,
           const __grid_constant__ CUtensorMap tm_u, const __grid_constant__ CUtensorMap tm_v, const __grid_constant__ CUtensorMap tm_t) {
    extern __shared__ unsigned char smem_raw[];
    const uint32_t sb = ((uint32_t)__cvta_generic_to_shared(smem_raw) + 1023u) & ~1023u;
    const int tid = threadIdx.x, lane = tid & 31, b = blockIdx.x;
    const int w = __shfl_sync(0xffffffffu, tid >> 5, 0);
    const int wq = w >> 2, w4 = w & 3;
    const int g = lane >> 2, t = lane & 3, mi = lane >> 3, rr = lane & 7;
    TRACE(0);

    uint32_t Cf[8][4];
    auto load_cf = [&]() {
        const int krow = rr + 8 * (mi >> 1);
#pragma unroll
        for (int j = 0; j < 8; j++) {
            const int c = 2 * j + (mi & 1);
            ldsm4t(Cf[j], sb + SM_C + krow * 256 + ((c & 8) << 4) + (((c & 7) ^ rr) << 4));
#pragma unroll
            for (int q = 0; q < 4; q++) Cf[j][q] = mul_bf16x2(Cf[j][q], 0x3F003F00u);
        }
    };
    uint32_t xAf[8][2];
    float agg[8][4];
    const uint32_t ident = (g == 2 * t) ? 0x3F80u : ((g == 2 * t + 1) ? 0x3F800000u : 0u);
    const int nslot = (w < 12) ? 5 : 4;
    auto load_node_frags = [&]() {
        const int mynode = lds8(sb + SM_TNODE + w * 8 + ((rr < nslot) ? rr : 0));
#pragma unroll
        for (int jp = 0; jp < 4; jp++) {
            const int c = 4 * jp + mi;
            const uint32_t off = mynode * 128 + (((c & 7) ^ (mynode & 7)) << 4);
            uint32_t q[4];
            ldsm4t(q, sb + SM_WA + (c >> 3) * 16384 + off);
            xAf[2 * jp][0] = q[0]; xAf[2 * jp][1] = q[1]; xAf[2 * jp + 1][0] = q[2]; xAf[2 * jp + 1][1] = q[3];
            ldsm4t(q, sb + SM_X + (c >> 3) * 10240 + off);
            mma1688_z(agg[2 * jp], q[0], q[1], ident);
            mma1688_z(agg[2 * jp + 1], q[2], q[3], ident);
        }
    };
    uint32_t bar_target = 0;
    constexpr int LT = 256;
    if (wq < 2) {
        uint32_t epoch = 0;
        {
            const int r = tid >> 4, c = tid & 15;
            cp16(sb + SM_C + r * 256 + ((c & 8) << 4) + (((c & 7) ^ (r & 7)) << 4), p.gw + (256 + r) * 128 + c * 8);
            cp_commit();
        }
        if (tid == 0) {
            asm volatile("ld.relaxed.gpu.global.u32 %0, [%1];" : "=r"(epoch) : "l"(p.bar) : "memory");
            for (int i = 0; i < 9; i++) mbar_init(sb + SM_BAR + i * 8, 1);
            asm volatile("fence.mbarrier_init.release.cluster;" ::: "memory");
            const uint32_t bx = sb + SM_BAR;
            mbar_expect(bx, 20480);
#pragma unroll
            for (int i = 0; i < 8; i++) mbar_expect(bx + 8 + i * 8, 16384);
            spin(START_DELAY);
            tma_load2d(sb + SM_X, &tm_x, 0, b * NPC, bx);
            tma_load2d(sb + SM_X + 10240, &tm_x, 64, b * NPC, bx);
            tma_load2d(sb + SM_R0, &tm_g, 0, 128, bx + 8);
            tma_load2d(sb + SM_R0 + 16384, &tm_g, 64, 128, bx + 16);
            tma_load2d(sb + SM_R0 + 2 * 16384, &tm_v, 0, 0, bx + 24);
            tma_load2d(sb + SM_R0 + 3 * 16384, &tm_v, 64, 0, bx + 32);
        }
        cp_wait<0>();
        asm volatile("bar.sync 6, 256;" ::: "memory");
        asm volatile("bar.arrive 8, 512;" ::: "memory");
        TRACE(1);
        float d0[40], d1[40];
        const uint32_t xt = sb + SM_X;
        const bool elect = (w4 == 0 && lane == 0);
        mbar_wait(sb + SM_BAR, 0);
#pragma unroll 1
        for (int r = 0; r < 2; r++) {
            const uint32_t wt0 = sb + (r ? SM_WA : SM_R0) + wq * 16384, wt1 = sb + (r ? SM_WU : SM_R0 + 32768) + wq * 16384;
            mbar_wait(sb + SM_BAR + 8 + (4 * r + wq) * 8, 0);
            TRACE(2 + 2 * r);
            gemm_issue(d0, wt0, xt);
            if (r == 0 && tid == 0) {
#pragma unroll
                for (int i = 0; i < 2; i++) {
                    tma_load2d(sb + SM_WA + i * 16384, &tm_g, i * 64, 0, sb + SM_BAR + 8 + (4 + i) * 8);
                    tma_load2d(sb + SM_WU + i * 16384, &tm_u, i * 64, 0, sb + SM_BAR + 8 + (6 + i) * 8);
                }
            }
            __syncwarp();
            mbar_wait(sb + SM_BAR + 8 + (4 * r + 2 + wq) * 8, 0);
            gemm_issue(d1, wt1, xt);
            if (r == 1) {
                asm volatile("bar.sync 4, 512;" ::: "memory");
                if (elect) {
                    asm volatile("cp.async.bulk.wait_group 0;" ::: "memory");
                    asm volatile("fence.proxy.async.global;" ::: "memory");
                    asm volatile("red.relaxed.gpu.global.add.u32 [%0], 1;" :: "l"(p.bar) : "memory");
                }
                if (tid == 0) {
                    const int e0 = b * ECH, ne = min(ECH, EE - e0);
                    asm volatile("cp.async.bulk.prefetch.L2.global [%0], %1;" :: "l"(p.e_attr + (size_t)e0 * 16), "r"(ne * 32) : "memory");
                }
                __syncwarp();
            }
            gemm_wait(d0);
            gemm_wait(d1);
            if (r == 0) wg_bar(1 + wq); else asm volatile("bar.sync 6, 256;" ::: "memory");
            gemm_store(d0, 0.5f, wt0, w4, lane);
            gemm_store(d1, r ? 0.5f : 0.25f, r ? xt + wq * 10240 : wt1, w4, lane);
            if (r == 0) {
                asm volatile("fence.proxy.async.shared::cta;" ::: "memory");
                wg_bar(1 + wq);
                if (elect) {
                    tma_store2d(&tm_t, wq * 64, b * NPC, wt0);
                    tma_store2d(&tm_t, (2 + wq) * 64, b * NPC, wt1);
                    asm volatile("cp.async.bulk.commit_group;" ::: "memory");
                }
                __syncwarp();
            }
            TRACE(3 + 2 * r);
        }
        load_cf();

        bar_target = (epoch / (2 * NCTA) + 1) * (2 * NCTA);
        TRACE(9);
    } else {
        const int lt = tid - LT;
        int ed[5], es[5];
        uint32_t epoch;
#pragma unroll
        for (int m = 0; m < 5; m++) {
            const int k = lt + m * LT, e = b * ECH + k;
            ed[m] = ((k < ECH) && (e < EE)) ? __ldg(p.dst + e) : -1;
        }
#pragma unroll
        for (int m = 0; m < 5; m++) {
            const int k = lt + m * LT, e = b * ECH + k;
            es[m] = ((k < ECH) && (e < EE)) ? __ldg(p.src + e) : 0;
        }
        asm volatile("ld.relaxed.gpu.global.u32 %0, [%1];" : "=r"(epoch) : "l"(p.bar) : "memory");
        if (lt < 136) sts32(sb + SM_HIST + lt * 4, 0);
        if (lt < 128) { sts32(sb + SM_KEYS + lt * 4, 0); sts32(sb + SM_TDEG + lt * 4, 0); }
        if (lt < 64) sts32(sb + SM_DBIN + lt * 4, 0);
        if (lt == 0) sts32(sb + SM_FLAG, 0);
        lt_bar();
        TRACE(24);
        {
            uint32_t jj[5], rk[5];
#pragma unroll
            for (int m = 0; m < 5; m++) {
                jj[m] = (ed[m] >= 0) ? (((uint32_t)ed[m] * 55189u) >> 22) : (132 + (lane & 3));
                rk[m] = atoms_add(sb + SM_HIST + jj[m] * 4, 1);
            }
#pragma unroll
            for (int m = 0; m < 5; m++) {
                const uint32_t loc = (uint32_t)ed[m] - jj[m] * NPC;
                const uint32_t q = (rk[m] * 43691u) >> 17;
                const uint32_t off = jj[m] * (PIECES * 16) + q * 16 + (rk[m] - 3 * q + 1) * 4;
                sts32(sb + SM_S + ((ed[m] >= 0 && rk[m] < XCAP) ? off : NCTA * PIECES * 16 + lane * 4),
                      (uint32_t)es[m] | (loc << 14) | ((uint32_t)(lt + m * LT) << 21));
            }
        }
        const uint32_t bar_q = epoch / (2 * NCTA);
        epoch = (bar_q + 1) & 0xFFFFFF;
        TRACE(25);
        lt_bar();
        {
            uint4 v[6]; uint32_t c[6];
#pragma unroll
            for (int m = 0; m < 6; m++) {
                const int pc = min(lt + m * LT, NCTA * PIECES - 1);
                v[m] = lds128(sb + SM_S + pc * 16);
                c[m] = lds32(sb + SM_HIST + ((pc * 6554) >> 16) * 4);
            }
#pragma unroll
            for (int m = 0; m < 6; m++) {
                const int pc = lt + m * LT;
                const int j = (pc * 6554) >> 16, q = pc - j * PIECES;
                if ((m < 5 || pc < NCTA * PIECES) && (q < 4 || c[m] > 3 * (q & ~1) || b >= 128)) {
                    v[m].x = (epoch << 8) | min(c[m], 255u);
                    st_piece(p.xch + (((j * (PIECES / 2) + (q >> 1)) * NCTA + b) * 2 + (q & 1)), v[m]);
                }
            }
        }
        TRACE(46);
        asm volatile("bar.arrive 4, 512;" ::: "memory");
        lt_bar();
        if (lt == 0) asm volatile("red.relaxed.gpu.global.add.u32 [%0], 1;" :: "l"(p.bar + 1) : "memory");
        asm volatile("bar.sync 8, 512;" ::: "memory");
        load_cf();
        if (lt == 0) {
            uint32_t v; int it = 0;
            const uint32_t target = bar_q * NCTA + NCTA / 2;
            do { asm volatile("ld.relaxed.gpu.global.u32 %0, [%1];" : "=r"(v) : "l"(p.bar + 1) : "memory"); }
            while ((int)(v - target) < 0 && ++it < SPIN_LIMIT);
        }
        lt_bar();
        TRACE(26);
        uint4 pv[6];
        const int pi5 = 128 + ((lt >> 1) & 3), pq5 = 2 * (lt >> 3) + (lt & 1);
        const uint4* px0 = p.xch + b * (NCTA * PIECES) + lt;
        const uint4* px5 = p.xch + b * (NCTA * PIECES) + (lt >> 3) * (2 * NCTA) + 256 + (lt & 7);
        const uint32_t tg = epoch << 8;
        auto fetch = [&](const uint4* a) {
            uint4 v = ld_piece(a);
            int it = 0;
            while (((v.x ^ tg) >> 8) && ++it < SPIN_LIMIT) { __nanosleep(100); v = ld_piece(a); }
            return v;
        };
        pv[0] = ld_piece(px0);
        pv[1] = ld_piece(px0 + 2 * NCTA);
        pv[5] = (lt < 4 * PIECES) ? ld_piece(px5) : make_uint4(tg, 0, 0, 0);
        for (int it = 0; (((pv[0].x ^ tg) | (pv[1].x ^ tg) | (pv[5].x ^ tg)) >> 8) && it < SPIN_LIMIT; it++) {
            __nanosleep(100);
            if ((pv[0].x ^ tg) >> 8) pv[0] = ld_piece(px0);
            if ((pv[1].x ^ tg) >> 8) pv[1] = ld_piece(px0 + 2 * NCTA);
            if ((pv[5].x ^ tg) >> 8) pv[5] = ld_piece(px5);
        }
        const int cnt = pv[0].x & 255, cnt5 = pv[5].x & 255;
#pragma unroll
        for (int m = 2; m < 5; m++) pv[m] = (cnt > 6 * m) ? ld_piece(px0 + m * (2 * NCTA)) : make_uint4(tg, 0, 0, 0);
        if (cnt > XCAP || cnt5 > XCAP) sts32(sb + SM_FLAG, 1);
        TRACE(27);
        const uint32_t dmy = (96 + lane) * 4;
        uint32_t ao[9], rk[9];
        auto count = [&](int m, int o) {
            const int nv = (m < 5) ? cnt - 3 * (2 * m + (lt & 1)) : cnt5 - 3 * pq5;
#pragma unroll
            for (int s = 0; s < 3; s++) {
                const uint32_t pl = (s == 0) ? pv[m].y : ((s == 1) ? pv[m].z : pv[m].w);
                ao[o + s] = (nv > s) ? ((pl >> 12) & 0x1FC) : dmy;
                rk[o + s] = atoms_add(sb + SM_KEYS + ao[o + s], 1);
            }
        };
        auto put = [&](int m, int o) {
            const uint32_t e0s = (uint32_t)(((m < 5) ? (lt >> 1) : pi5) * ECH) << 14;
#pragma unroll
            for (int s = 0; s < 3; s++) {
                const uint32_t pl = (s == 0) ? pv[m].y : ((s == 1) ? pv[m].z : pv[m].w);
                const bool ok = ao[o + s] < 96 * 4 && rk[o + s] < NCAP;
                sts32(sb + SM_NL + (ok ? ao[o + s] * NCAP + rk[o + s] * 4 : NPC * NCAP * 4 + lane * 4), (pl & 0x3FFF) + ((pl >> 21) << 14) + e0s);
            }
        };
        count(0, 0);
        count(1, 3);
        const bool has5 = lt < 64;
        if (has5) count(5, 6);
        put(0, 0);
        put(1, 3);
        if (has5) put(5, 6);
        if (((pv[2].x ^ tg) | (pv[3].x ^ tg) | (pv[4].x ^ tg)) >> 8) {
#pragma unroll
            for (int m = 2; m < 5; m++) if (cnt > 6 * m) pv[m] = fetch(px0 + m * (2 * NCTA));
        }
#pragma unroll
        for (int m = 2; m < 5; m++) {
            if (__any_sync(0xffffffffu, cnt > 6 * m)) { count(m, 0); put(m, 0); }
        }
        TRACE(28);
        lt_bar();
        if (lt < 96) {
            const uint32_t deg = (lt < NPC) ? lds32(sb + SM_KEYS + lt * 4) : 0;
            const uint32_t bin = 63 - min(deg, 63u);
            const uint32_t r0 = atoms_add_p(lt < NPC, sb + SM_DBIN + bin * 4, 1);
            if (deg > NCAP) sts32(sb + SM_FLAG, 1);
            asm volatile("bar.sync 5, 96;" ::: "memory");
            const uint2 c2 = lds64(sb + SM_DBIN + lane * 8);
            uint32_t inc = c2.x + c2.y;
#pragma unroll
            for (int o = 1; o < 32; o <<= 1) { const uint32_t u = __shfl_up_sync(0xffffffffu, inc, o); if (lane >= o) inc += u; }
            const uint32_t ex = inc - c2.x - c2.y;
            const uint32_t pe = __shfl_sync(0xffffffffu, ex, bin >> 1), p0 = __shfl_sync(0xffffffffu, c2.x, bin >> 1);
            const int rank = pe + ((bin & 1) ? p0 : 0) + r0;
            const int k = rank >> 4, pos = rank & 15;
            const int tile = (k == 4) ? 11 - pos : ((pos < 4) ? 12 + ((k & 1) ? 3 - pos : pos) : ((k < 3) ? pos - 4 : 15 - pos));
            if (lt < NPC) {
                sts32(sb + SM_TDEG + (tile * 8 + k) * 4, deg);
                sts8(sb + SM_TNODE + tile * 8 + k, lt);
            }
        }
        TRACE(29);
        TRACE(30);
    }
    TRACE(31);
    __syncthreads();
    TRACE(32);
    bool slow = lds32(sb + SM_FLAG) != 0;

    constexpr uint32_t RD = SM_R1 - SM_R0;
    const uint32_t ring0 = sb + SM_R0 + w * STAGE;
    const char* tab_l = p.table + lane * 16;
    asm volatile("" : "+l"(tab_l));
    const char* e_l = (const char*)p.e_attr + (mi & 1) * 16;
    asm volatile("" : "+l"(e_l));
    const uint32_t cpo = lane * 16;
    const uint32_t elo = 4096 + rr * 32 + (((mi & 1) ^ ((rr >> 2) & 1)) << 4);
    const uint32_t lsrc = sb + SM_LSE + w * TCAP * 4, lid = sb + SM_LID + w * TCAP;
    const uint32_t lec = rr * 4;

    auto issue_full = [&](uint32_t lp, uint32_t dl) {
        const uint4 s0 = lds128(lp), s1 = lds128(lp + 16);
        const uint32_t eo = lds32(lp + lec);
        const uint32_t sv[8] = {s0.x, s0.y, s0.z, s0.w, s1.x, s1.y, s1.z, s1.w};
#pragma unroll
        for (int j = 0; j < 8; j++) cp16(ring0 + dl + (cpo ^ (j << 4)) + j * 512, madw(sv[j] & 0x3FFF, 512, tab_l));
        cp16(ring0 + dl + elo, madw(eo >> 14, 32, e_l));
    };
    auto issue0 = [&]() {
        const int cnt = lds32(sb + SM_TCNT + w * 4), nit = (cnt + 7) >> 3;
        if (nit > 0) {
            const int pad = nit * 8 - cnt;
            const uint4 s0 = lds128(lsrc), s1 = lds128(lsrc + 16);
            const uint32_t eo = lds32(lsrc + lec);
            const uint32_t sv[8] = {s0.x, s0.y, s0.z, s0.w, s1.x, s1.y, s1.z, s1.w};
#pragma unroll
            for (int j = 0; j < 8; j++) cp16z(ring0 + (cpo ^ (j << 4)) + j * 512, madw(sv[j] & 0x3FFF, 512, tab_l), (j >= pad) ? 16 : 0);
            cp16z(ring0 + elo, madw(eo >> 14, 32, e_l), (rr >= pad) ? 16 : 0);
        }
        cp_commit();
    };
    auto issue1 = [&]() {
        if ((int)lds32(sb + SM_TCNT + w * 4) > 8) issue_full(lsrc + 32, RD);
        cp_commit();
    };
    uint32_t bar_v = 0;
    bool over = false;
    if (tid == 0) asm volatile("ld.relaxed.gpu.global.u32 %0, [%1];" : "=r"(bar_v) : "l"(p.bar) : "memory");
    if (!slow) {
        const uint2 tn = lds64(sb + SM_TNODE + w * 8);
        const uint4 dg = lds128(sb + SM_TDEG + w * 32);
        const uint32_t p1 = dg.x, p2 = p1 + dg.y, p3 = p2 + dg.z, p4 = p3 + dg.w, tot = p4 + lds32(sb + SM_TDEG + w * 32 + 16);
        const uint32_t pad = (0u - tot) & 7u;
        if (lane == 0) sts32(sb + SM_TCNT + w * 4, tot);
        over = tot + pad > TCAP;
        uint32_t wd[TCAP / 32], sl[TCAP / 32];
#pragma unroll
        for (int r = 0; r < TCAP / 32; r++) {
            const uint32_t q = lane + 32 * r - pad;
            sl[r] = (q >= p1) + (q >= p2) + (q >= p3) + (q >= p4);
            const uint32_t pre = (q >= p4) ? p4 : ((q >= p3) ? p3 : ((q >= p2) ? p2 : ((q >= p1) ? p1 : 0)));
            const uint32_t node = prmt(tn.x, tn.y, sl[r]) & 0xFF;
            wd[r] = lds32(sb + SM_NL + ((q < tot) ? (node * NCAP + q - pre) * 4 : 0));
        }
#pragma unroll
        for (int r = 0; r < TCAP / 32; r++) {
            const uint32_t q = lane + 32 * r - pad;
            sts32(lsrc + (lane + 32 * r) * 4, (q < tot) ? wd[r] : 0);
            sts8(lid + lane + 32 * r, (q < tot) ? sl[r] * 16 : 0x7F);
        }
    }
    TRACE(10);
    if (tid == 0) {
        int it = 0;
        while ((int)(bar_v - bar_target) < 0 && ++it < SPIN_LIMIT)
            asm volatile("ld.relaxed.gpu.global.u32 %0, [%1];" : "=r"(bar_v) : "l"(p.bar) : "memory");
    }
    slow = __syncthreads_or(slow || over);
    TRACE(11);
    if (!slow) {
        issue0();
        issue1();
    } else {
        if (tid < NPC) sts8(sb + SM_TNODE + (tid & 15) * 8 + (tid >> 4), tid);
        __syncthreads();
    }
    TRACE(33);
    load_node_frags();
    TRACE(34);

    const uint32_t ldo = rr * 512 + ((mi ^ rr) << 4);
    const uint32_t sel = (g | ((8 | g) << 4) | (g << 8) | ((8 | g) << 12)) |
                         (((2 * t) | ((8 | (2 * t)) << 4) | ((2 * t + 1) << 8) | ((8 | (2 * t + 1)) << 12)) << 16);
    const uint32_t gg = (g * 16) | ((g * 16) << 16);
    const uint32_t tt = (t * 32) | ((t * 32 + 16) << 16);

    auto compute = [&](uint32_t st, uint32_t idp) {
        uint32_t eb[2];
        ldsm2(eb, st + elo);
        const uint2 iw = lds64(idp);
        const uint32_t sx = seteq_bf16x2(prmt(iw.x, iw.y, sel), tt);
        const uint32_t sa = seteq_bf16x2(prmt(iw.x, iw.y, sel >> 16), gg);
#pragma unroll
        for (int jj = 0; jj < 4; jj++) {
            uint32_t xb[4], hv[4];
            const uint32_t la = st + (ldo ^ ((jj & 1) << 6)) + (jj >> 1) * 128;
            ldsm4(xb, la);
            ldsm4t(hv, la + 256);
#pragma unroll
            for (int u = 0; u < 2; u++) {
                const int j = 2 * jj + u;
                float d[4];
                mma16816_z(d, Cf[j][0], Cf[j][1], Cf[j][2], Cf[j][3], eb[0], eb[1]);
                mma1688(d, xAf[j][0], xAf[j][1], sx);
                mma16816(d, ident, 0u, 0u, ident, xb[2 * u], xb[2 * u + 1]);
                const uint32_t m0 = fma_bf16x2(pack_bf16(tanh_ap(d[0]), tanh_ap(d[1])), hv[2 * u], hv[2 * u]);
                const uint32_t m1 = fma_bf16x2(pack_bf16(tanh_ap(d[2]), tanh_ap(d[3])), hv[2 * u + 1], hv[2 * u + 1]);
                mma1688(agg[j], m0, m1, sa);
            }
        }
    };

    const int nseg = slow ? NSEG : 1;
#pragma unroll 1
    for (int seg = 0; seg < nseg; seg++) {
        if (slow) {
            __syncthreads();
            if (tid < 16) sts32(sb + SM_TCNT + tid * 4, 0);
            __syncthreads();
            const int e = seg * TCAP + tid;
            int loc = -1; uint32_t r = 0;
            if (tid < TCAP && e < EE) {
                const int dd = __ldg(p.dst + e) - b * NPC;
                if (dd >= 0 && dd < NPC) { loc = dd; r = atoms_add(sb + SM_TCNT + (loc & 15) * 4, 1); }
            }
            __syncthreads();
            if (loc >= 0) {
                const uint32_t tile = loc & 15, tot = lds32(sb + SM_TCNT + tile * 4);
                const uint32_t pos = tile * TCAP + ((0u - tot) & 7u) + r;
                sts32(sb + SM_LSE + pos * 4, (uint32_t)__ldg(p.src + e) | ((uint32_t)e << 14));
                sts8(sb + SM_LID + pos, (loc >> 4) << 4);
            }
            const int pad = (0 - (int)lds32(sb + SM_TCNT + w * 4)) & 7;
            if (lane < pad) { sts8(sb + SM_LID + w * TCAP + lane, 0x7F); sts32(sb + SM_LSE + (w * TCAP + lane) * 4, 0); }
            __syncthreads();
            issue0();
            issue1();
        }
        const int nit = __shfl_sync(0xffffffffu, ((int)lds32(sb + SM_TCNT + w * 4) + 7) >> 3, 0);
        uint32_t st = ring0, so = ring0 + RD, lp = lsrc + 32, idp = lid;
        const uint32_t lend = lsrc + nit * 32;
        constexpr int AVG_NIT = (EE + NCTA * 128 - 1) / (NCTA * 128);
        constexpr int HEAVY = EE / NN * NPC * 207 / 200;
        const int ctot = __reduce_add_sync(0xffffffffu, (lane < 16) ? (int)lds32(sb + SM_TCNT + lane * 4) : 0);
        if (nit <= AVG_NIT && ctot <= HEAVY) {
#pragma unroll 1
            for (; lp <= lend; lp += 32, idp += 8) {
                if (idp == lid) cp_wait<1>(); else cp_wait<0>();
                __syncwarp();
                if (idp != lid && lp < lend) issue_full(lp, so - ring0);
                cp_commit();
                compute(st, idp);
                const uint32_t tmp = st; st = so; so = tmp;
            }
        } else {
#pragma unroll 1
            for (; lp <= lend; lp += 32, idp += 8) {
                cp_wait<1>();
                __syncwarp();
                compute(st, idp);
                __syncwarp();
                if (lp + 32 < lend) issue_full(lp + 32, st - ring0);
                cp_commit();
                const uint32_t tmp = st; st = so; so = tmp;
            }
        }
        cp_wait<0>();
        __syncwarp();
    }
    TRACE(35);

    {
        uint32_t o[8][2];
#pragma unroll
        for (int j = 0; j < 8; j++) {
            float v[4];
#pragma unroll
            for (int q = 0; q < 4; q++) { const float h = agg[j][q]; v[q] = fmaf(h, tanh_ap(h), h); }
            o[j][0] = pack_bf16(v[0], v[1]); o[j][1] = pack_bf16(v[2], v[3]);
        }
#pragma unroll
        for (int jp = 0; jp < 4; jp++) {
            const int c = 4 * jp + mi;
            stsm4t(ring0 + rr * 256 + ((c & 8) << 4) + (((c & 7) ^ rr) << 4), o[2 * jp][0], o[2 * jp][1], o[2 * jp + 1][0], o[2 * jp + 1][1]);
        }
        __syncwarp();
#pragma unroll
        for (int i = 0; i < 3; i++) {
            const int idx = lane + 32 * i, row = idx >> 4, c = idx & 15;
            const int nd = b * NPC + (int)lds8(sb + SM_TNODE + w * 8 + (row & 7));
            if (row < nslot && nd < NN) {
                const uint4 v = lds128(ring0 + row * 256 + ((c & 8) << 4) + (((c & 7) ^ row) << 4));
                *(uint4*)((char*)p.out + (size_t)nd * 256 + c * 16) = v;
            }
        }
    }
    TRACE(36);
}

__device__ __align__(16) bf16 g_fb_xa[NN * 128];
__device__ __align__(16) float g_fb_h[NN * 128];

__global__ void fb_node_kernel(const bf16* x, const bf16* uw, const bf16* vw, const bf16* gw, bf16* table) {
    __shared__ float xs[128];
    const int n = blockIdx.x, f = threadIdx.x;
    xs[f] = __bfloat162float(x[n * 128 + f]);
    __syncthreads();
    float a = 0.f, bb = 0.f, v = 0.f, u = 0.f;
    for (int k = 0; k < 128; k++) {
        const float xv = xs[k];
        a += xv * __bfloat162float(gw[k * 128 + f]);
        bb += xv * __bfloat162float(gw[(128 + k) * 128 + f]);
        v += xv * __bfloat162float(vw[k * 128 + f]);
        u += xv * __bfloat162float(uw[k * 128 + f]);
    }
    table[n * 256 + f] = __float2bfloat16(0.5f * bb);
    table[n * 256 + 128 + f] = __float2bfloat16(0.25f * v);
    g_fb_xa[n * 128 + f] = __float2bfloat16(0.5f * a);
    g_fb_h[n * 128 + f] = 0.5f * u;
}
__global__ void fb_edge_kernel(const bf16* e_attr, const int* src, const int* dst, const bf16* gw, const bf16* table) {
    const int e = blockIdx.x, f = threadIdx.x, s = src[e], d = dst[e];
    float z = 0.f;
    for (int k = 0; k < 16; k++) z += __bfloat162float(e_attr[e * 16 + k]) * __bfloat162float(gw[(256 + k) * 128 + f]);
    z = 0.5f * z + __bfloat162float(g_fb_xa[d * 128 + f]) + __bfloat162float(table[s * 256 + f]);
    const float hv = __bfloat162float(table[s * 256 + 128 + f]);
    atomicAdd(&g_fb_h[d * 128 + f], fmaf(hv, tanhf(z), hv));
}
__global__ void fb_out_kernel(bf16* out) {
    const int i = blockIdx.x * 128 + threadIdx.x;
    const float h = g_fb_h[i];
    out[i] = __float2bfloat16(fmaf(h, tanhf(h), h));
}

typedef CUresult (*EncodeFn)(CUtensorMap*, CUtensorMapDataType, cuuint32_t, void*, const cuuint64_t*, const cuuint64_t*,
                             const cuuint32_t*, const cuuint32_t*, CUtensorMapInterleave, CUtensorMapSwizzle,
                             CUtensorMapL2promotion, CUtensorMapFloatOOBfill);

static void make_map(EncodeFn enc, CUtensorMap* tm, const void* base, int rows, int cols, int box_rows) {
    cuuint64_t dims[2] = {(cuuint64_t)cols, (cuuint64_t)rows};
    cuuint64_t strides[1] = {(cuuint64_t)cols * 2};
    cuuint32_t box[2] = {64, (cuuint32_t)box_rows};
    cuuint32_t es[2] = {1, 1};
    enc(tm, CU_TENSOR_MAP_DATA_TYPE_BFLOAT16, 2, (void*)base, dims, strides, box, es, CU_TENSOR_MAP_INTERLEAVE_NONE,
        CU_TENSOR_MAP_SWIZZLE_128B, CU_TENSOR_MAP_L2_PROMOTION_NONE, CU_TENSOR_MAP_FLOAT_OOB_FILL_NONE);
}

}

extern "C" void kernel_launch(void* const* d_in, const int* in_sizes, int n_in, void* d_out, int out_size) {
    using namespace egc;
    (void)in_sizes; (void)n_in; (void)out_size;
    static EncodeFn enc = nullptr;
    static void* table = nullptr;
    static void* xch = nullptr;
    static void* bar = nullptr;
    static bool persistent = false;
    if (!enc) {
        void* fn = nullptr;
        cudaDriverEntryPointQueryResult qr;
        cudaGetDriverEntryPoint("cuTensorMapEncodeTiled", &fn, cudaEnableDefault, &qr);
        enc = (EncodeFn)fn;
        cudaGetSymbolAddress(&table, g_table);
        cudaGetSymbolAddress(&xch, g_xch);
        cudaGetSymbolAddress(&bar, g_bar);
        cudaFuncSetAttribute(egc_kernel, cudaFuncAttributeMaxDynamicSharedMemorySize, SMEM_BYTES);
        int dev = 0, sms = 0, per_sm = 0;
        cudaGetDevice(&dev);
        cudaDeviceGetAttribute(&sms, cudaDevAttrMultiProcessorCount, dev);
        cudaOccupancyMaxActiveBlocksPerMultiprocessor(&per_sm, egc_kernel, NTHR, SMEM_BYTES);
        persistent = enc != nullptr && sms * per_sm >= NCTA;
    }
    if (!persistent) {
        const bf16* x = (const bf16*)d_in[0];
        fb_node_kernel<<<NN, 128, 0, cudaStreamPerThread>>>(x, (const bf16*)d_in[4], (const bf16*)d_in[5], (const bf16*)d_in[6], (bf16*)table);
        fb_edge_kernel<<<EE, 128, 0, cudaStreamPerThread>>>((const bf16*)d_in[1], (const int*)d_in[2], (const int*)d_in[3], (const bf16*)d_in[6], (const bf16*)table);
        fb_out_kernel<<<NN, 128, 0, cudaStreamPerThread>>>((bf16*)d_out);
        return;
    }
    CUtensorMap tm_x, tm_g, tm_u, tm_v, tm_t;
    make_map(enc, &tm_x, d_in[0], NN, 128, 80);
    make_map(enc, &tm_u, d_in[4], 128, 128, 128);
    make_map(enc, &tm_v, d_in[5], 128, 128, 128);
    make_map(enc, &tm_g, d_in[6], 272, 128, 128);
    make_map(enc, &tm_t, table, NN, 256, NPC);
    Params p;
    p.e_attr = (const bf16*)d_in[1];
    p.src = (const int*)d_in[2];
    p.dst = (const int*)d_in[3];
    p.gw = (const bf16*)d_in[6];
    p.out = (bf16*)d_out;
    p.bar = (unsigned*)bar;
    p.xch = (uint4*)xch;
    p.table = (const char*)table;
    egc_kernel<<<NCTA, NTHR, SMEM_BYTES, cudaStreamPerThread>>>(p, tm_x, tm_g, tm_u, tm_v, tm_t);
}
```

```cpp
#include <cuda_runtime.h>
#include <cuda_bf16.h>
#include <cuda.h>
#include <stdint.h>
#include <type_traits>

namespace egc {

typedef __nv_bfloat16 bf16;

constexpr int NN = 10000, EE = 160000;
constexpr int NCTA = 132, NPC = 76, ECH = 1216, NTHR = 512;
constexpr int PIECES = 10, XCAP = 3 * PIECES;
constexpr int TCAP = 96;
constexpr int NSEG = (EE + TCAP - 1) / TCAP;
constexpr int SPIN_LIMIT = 1 << 20;
constexpr uint32_t START_DELAY = 420;

constexpr int STAGE = 4352;
constexpr int SM_R0 = 0;
constexpr int SM_R1 = 16 * STAGE;
constexpr int SM_S = SM_R1;
constexpr int SM_WU = SM_R1 + 8 * STAGE;
constexpr int SM_WA = SM_R1 + 16 * STAGE;
constexpr int SM_X = SM_WA + 32768;
constexpr int SM_C = SM_X + 20480;
constexpr int SM_LSE = SM_C + 4096;
constexpr int SM_LID = SM_LSE + 6144 + 128;
constexpr int SM_HIST = SM_LID + 1536 + 32;
constexpr int SM_KEYS = SM_HIST + 544;
constexpr int SM_CURS = SM_KEYS + 512;
constexpr int SM_DBIN = SM_CURS + 512;
constexpr int SM_TDEG = SM_DBIN + 256;
constexpr int SM_TNODE = SM_TDEG + 512;
constexpr int SM_TCNT = SM_TNODE + 128;
constexpr int SM_FLAG = SM_TCNT + 64;
constexpr int NCAP = 40;
constexpr int SM_NL = SM_FLAG + 16;
constexpr int SM_BAR = SM_NL + NPC * NCAP * 4 + 128;
constexpr int SM_TRACE = SM_BAR + 9 * 8 + 8;
constexpr int SM_END = SM_TRACE + 2 * 48 * 4;
constexpr int SMEM_BYTES = SM_END + 1024;

__device__ __align__(1024) uint4 g_table[NN * 32];
__device__ __align__(1024) uint4 g_xch[NCTA * NCTA * PIECES];
__device__ __align__(128) unsigned g_bar[32];
#define TRACE(i) do {} while (0)

__device__ __forceinline__ void mma16816(float* d, uint32_t a0, uint32_t a1, uint32_t a2, uint32_t a3, uint32_t b0, uint32_t b1) {
    asm("mma.sync.aligned.m16n8k16.row.col.f32.bf16.bf16.f32 {%0,%1,%2,%3}, {%4,%5,%6,%7}, {%8,%9}, {%0,%1,%2,%3};"
        : "+f"(d[0]), "+f"(d[1]), "+f"(d[2]), "+f"(d[3]) : "r"(a0), "r"(a1), "r"(a2), "r"(a3), "r"(b0), "r"(b1));
}
__device__ __forceinline__ void mma16816_z(float* d, uint32_t a0, uint32_t a1, uint32_t a2, uint32_t a3, uint32_t b0, uint32_t b1) {
    asm("mma.sync.aligned.m16n8k16.row.col.f32.bf16.bf16.f32 {%0,%1,%2,%3}, {%4,%5,%6,%7}, {%8,%9}, {%10,%10,%10,%10};"
        : "=f"(d[0]), "=f"(d[1]), "=f"(d[2]), "=f"(d[3]) : "r"(a0), "r"(a1), "r"(a2), "r"(a3), "r"(b0), "r"(b1), "f"(0.f));
}
__device__ __forceinline__ void mma1688(float* d, uint32_t a0, uint32_t a1, uint32_t b0) {
    asm("mma.sync.aligned.m16n8k8.row.col.f32.bf16.bf16.f32 {%0,%1,%2,%3}, {%4,%5}, {%6}, {%0,%1,%2,%3};"
        : "+f"(d[0]), "+f"(d[1]), "+f"(d[2]), "+f"(d[3]) : "r"(a0), "r"(a1), "r"(b0));
}
__device__ __forceinline__ void mma1688_z(float* d, uint32_t a0, uint32_t a1, uint32_t b0) {
    asm("mma.sync.aligned.m16n8k8.row.col.f32.bf16.bf16.f32 {%0,%1,%2,%3}, {%4,%5}, {%6}, {%7,%7,%7,%7};"
        : "=f"(d[0]), "=f"(d[1]), "=f"(d[2]), "=f"(d[3]) : "r"(a0), "r"(a1), "r"(b0), "f"(0.f));
}
__device__ __forceinline__ void ldsm4(uint32_t* r, uint32_t addr) {
    asm volatile("ldmatrix.sync.aligned.m8n8.x4.shared.b16 {%0,%1,%2,%3}, [%4];" : "=r"(r[0]), "=r"(r[1]), "=r"(r[2]), "=r"(r[3]) : "r"(addr) : "memory");
}
__device__ __forceinline__ void ldsm4t(uint32_t* r, uint32_t addr) {
    asm volatile("ldmatrix.sync.aligned.m8n8.x4.trans.shared.b16 {%0,%1,%2,%3}, [%4];" : "=r"(r[0]), "=r"(r[1]), "=r"(r[2]), "=r"(r[3]) : "r"(addr) : "memory");
}
__device__ __forceinline__ void ldsm2(uint32_t* r, uint32_t addr) {
    asm volatile("ldmatrix.sync.aligned.m8n8.x2.shared.b16 {%0,%1}, [%2];" : "=r"(r[0]), "=r"(r[1]) : "r"(addr) : "memory");
}
__device__ __forceinline__ void stsm4t(uint32_t addr, uint32_t r0, uint32_t r1, uint32_t r2, uint32_t r3) {
    asm volatile("stmatrix.sync.aligned.m8n8.x4.trans.shared.b16 [%0], {%1,%2,%3,%4};" :: "r"(addr), "r"(r0), "r"(r1), "r"(r2), "r"(r3) : "memory");
}
__device__ __forceinline__ float tanh_ap(float x) { float r; asm("tanh.approx.f32 %0, %1;" : "=f"(r) : "f"(x)); return r; }
__device__ __forceinline__ uint32_t pack_bf16(float lo, float hi) { uint32_t r; asm("cvt.rn.bf16x2.f32 %0, %1, %2;" : "=r"(r) : "f"(hi), "f"(lo)); return r; }
__device__ __forceinline__ uint32_t fma_bf16x2(uint32_t a, uint32_t b, uint32_t c) { uint32_t r; asm("fma.rn.bf16x2 %0, %1, %2, %3;" : "=r"(r) : "r"(a), "r"(b), "r"(c)); return r; }
__device__ __forceinline__ uint32_t mul_bf16x2(uint32_t a, uint32_t b) { uint32_t r; asm("mul.rn.bf16x2 %0, %1, %2;" : "=r"(r) : "r"(a), "r"(b)); return r; }
__device__ __forceinline__ uint32_t seteq_bf16x2(uint32_t a, uint32_t b) { uint32_t r; asm("set.eq.bf16x2.bf16x2 %0, %1, %2;" : "=r"(r) : "r"(a), "r"(b)); return r; }
__device__ __forceinline__ uint32_t prmt(uint32_t a, uint32_t b, uint32_t s) { uint32_t r; asm("prmt.b32 %0, %1, %2, %3;" : "=r"(r) : "r"(a), "r"(b), "r"(s)); return r; }
__device__ __forceinline__ uint32_t shl_clamp(uint32_t a, uint32_t s) { uint32_t r; asm("shl.b32 %0, %1, %2;" : "=r"(r) : "r"(a), "r"(s)); return r; }
__device__ __forceinline__ void cp16(uint32_t dst, const void* src) { asm volatile("cp.async.cg.shared.global [%0], [%1], 16;" :: "r"(dst), "l"(src) : "memory"); }
__device__ __forceinline__ void cp16z(uint32_t dst, const void* src, uint32_t sz) { asm volatile("cp.async.cg.shared.global [%0], [%1], 16, %2;" :: "r"(dst), "l"(src), "r"(sz) : "memory"); }
__device__ __forceinline__ const void* madw(uint32_t a, uint32_t m, const void* base) {
    const void* r; asm("mad.wide.u32 %0, %1, %2, %3;" : "=l"(r) : "r"(a), "r"(m), "l"(base)); return r;
}
__device__ __forceinline__ void cp16_p(bool p, uint32_t dst, const void* src) {
    asm volatile("{\n.reg .pred p;\nsetp.ne.u32 p, %2, 0;\n@p cp.async.cg.shared.global [%0], [%1], 16;\n}" :: "r"(dst), "l"(src), "r"((uint32_t)p) : "memory");
}
__device__ __forceinline__ void cp_commit() { asm volatile("cp.async.commit_group;" ::: "memory"); }
template <int N> __device__ __forceinline__ void cp_wait() { asm volatile("cp.async.wait_group %0;" :: "n"(N) : "memory"); }
__device__ __forceinline__ uint4 lds128(uint32_t a) { uint4 v; asm volatile("ld.shared.v4.u32 {%0,%1,%2,%3}, [%4];" : "=r"(v.x), "=r"(v.y), "=r"(v.z), "=r"(v.w) : "r"(a) : "memory"); return v; }
__device__ __forceinline__ uint2 lds64(uint32_t a) { uint2 v; asm volatile("ld.shared.v2.u32 {%0,%1}, [%2];" : "=r"(v.x), "=r"(v.y) : "r"(a) : "memory"); return v; }
__device__ __forceinline__ uint32_t lds32(uint32_t a) { uint32_t v; asm volatile("ld.shared.u32 %0, [%1];" : "=r"(v) : "r"(a) : "memory"); return v; }
__device__ __forceinline__ uint32_t lds8(uint32_t a) { uint32_t v; asm volatile("ld.shared.u8 %0, [%1];" : "=r"(v) : "r"(a) : "memory"); return v; }
__device__ __forceinline__ void sts32(uint32_t a, uint32_t v) { asm volatile("st.shared.u32 [%0], %1;" :: "r"(a), "r"(v) : "memory"); }
__device__ __forceinline__ void sts8(uint32_t a, uint32_t v) { asm volatile("st.shared.u8 [%0], %1;" :: "r"(a), "r"(v) : "memory"); }
__device__ __forceinline__ void sts128(uint32_t a, uint4 v) { asm volatile("st.shared.v4.u32 [%0], {%1,%2,%3,%4};" :: "r"(a), "r"(v.x), "r"(v.y), "r"(v.z), "r"(v.w) : "memory"); }
__device__ __forceinline__ uint32_t atoms_add(uint32_t a, uint32_t v) { uint32_t r; asm volatile("atom.shared.add.u32 %0, [%1], %2;" : "=r"(r) : "r"(a), "r"(v) : "memory"); return r; }
__device__ __forceinline__ void reds_add(uint32_t a, uint32_t v) { asm volatile("red.shared.add.u32 [%0], %1;" :: "r"(a), "r"(v) : "memory"); }
__device__ __forceinline__ uint32_t atoms_add_p(bool p, uint32_t a, uint32_t v) {
    uint32_t r = 0;
    asm volatile("{\n.reg .pred p;\nsetp.ne.u32 p, %3, 0;\n@p atom.shared.add.u32 %0, [%1], %2;\n}" : "+r"(r) : "r"(a), "r"(v), "r"((uint32_t)p) : "memory");
    return r;
}
__device__ __forceinline__ uint32_t lds32_p(bool p, uint32_t a) {
    uint32_t r = 0;
    asm volatile("{\n.reg .pred p;\nsetp.ne.u32 p, %2, 0;\n@p ld.shared.u32 %0, [%1];\n}" : "+r"(r) : "r"(a), "r"((uint32_t)p) : "memory");
    return r;
}
__device__ __forceinline__ void sts32_p(bool p, uint32_t a, uint32_t v) {
    asm volatile("{\n.reg .pred p;\nsetp.ne.u32 p, %2, 0;\n@p st.shared.u32 [%0], %1;\n}" :: "r"(a), "r"(v), "r"((uint32_t)p) : "memory");
}
__device__ __forceinline__ void sts8_p(bool p, uint32_t a, uint32_t v) {
    asm volatile("{\n.reg .pred p;\nsetp.ne.u32 p, %2, 0;\n@p st.shared.u8 [%0], %1;\n}" :: "r"(a), "r"(v), "r"((uint32_t)p) : "memory");
}
__device__ __forceinline__ void st_piece(uint4* p, uint4 v) {
    asm volatile("{\n.reg .b128 q;\n.reg .b64 lo, hi;\nmov.b64 lo, {%1,%2};\nmov.b64 hi, {%3,%4};\nmov.b128 q, {lo, hi};\nst.relaxed.gpu.global.b128 [%0], q;\n}"
                 :: "l"(p), "r"(v.x), "r"(v.y), "r"(v.z), "r"(v.w) : "memory");
}
__device__ __forceinline__ uint4 ld_piece(const uint4* p) {
    uint4 v;
    asm volatile("{\n.reg .b128 q;\n.reg .b64 lo, hi;\nld.relaxed.gpu.global.b128 q, [%4];\nmov.b128 {lo, hi}, q;\nmov.b64 {%0,%1}, lo;\nmov.b64 {%2,%3}, hi;\n}"
                 : "=r"(v.x), "=r"(v.y), "=r"(v.z), "=r"(v.w) : "l"(p) : "memory");
    return v;
}
__device__ __forceinline__ void mbar_init(uint32_t bar, uint32_t cnt) { asm volatile("mbarrier.init.shared::cta.b64 [%0], %1;" :: "r"(bar), "r"(cnt) : "memory"); }
__device__ __forceinline__ void mbar_expect(uint32_t bar, uint32_t bytes) { asm volatile("mbarrier.arrive.expect_tx.shared::cta.b64 _, [%0], %1;" :: "r"(bar), "r"(bytes) : "memory"); }
__device__ __forceinline__ void mbar_wait(uint32_t bar, uint32_t parity) {
    uint32_t ok; int it = 0;
    do {
        asm volatile("{\n.reg .pred p;\nmbarrier.try_wait.parity.shared::cta.b64 p, [%1], %2;\nselp.u32 %0, 1, 0, p;\n}" : "=r"(ok) : "r"(bar), "r"(parity) : "memory");
    } while (!ok && ++it < (1 << 22));
}
__device__ __forceinline__ void tma_load2d(uint32_t dst, const CUtensorMap* tm, int c0, int c1, uint32_t bar) {
    asm volatile("cp.async.bulk.tensor.2d.shared::cluster.global.mbarrier::complete_tx::bytes [%0], [%1, {%3, %4}], [%2];"
                 :: "r"(dst), "l"(tm), "r"(bar), "r"(c0), "r"(c1) : "memory");
}
__device__ __forceinline__ void tma_load2d_mc(uint32_t dst, const CUtensorMap* tm, int c0, int c1, uint32_t bar) {
    asm volatile("cp.async.bulk.tensor.2d.shared::cluster.global.mbarrier::complete_tx::bytes.multicast::cluster [%0], [%1, {%3, %4}], [%2], %5;"
                 :: "r"(dst), "l"(tm), "r"(bar), "r"(c0), "r"(c1), "h"((uint16_t)3) : "memory");
}
__device__ __forceinline__ void tma_store2d(const CUtensorMap* tm, int c0, int c1, uint32_t src) {
    asm volatile("cp.async.bulk.tensor.2d.global.shared::cta.bulk_group [%0, {%2, %3}], [%1];"
                 :: "l"(tm), "r"(src), "r"(c0), "r"(c1) : "memory");
}
__device__ __forceinline__ void spin(uint32_t cycles) {
    uint32_t c0, c1;
    asm volatile("mov.u32 %0, %%clock;" : "=r"(c0));
    do { asm volatile("mov.u32 %0, %%clock;" : "=r"(c1)); } while (c1 - c0 < cycles);
}
__device__ __forceinline__ void lt_bar() { asm volatile("bar.sync 3, 256;" ::: "memory"); }
__device__ __forceinline__ void wg_bar(int id) { asm volatile("bar.sync %0, 128;" :: "r"(id) : "memory"); }

__device__ __forceinline__ void wgmma_n80(float (&d)[40], uint64_t da, uint64_t db, int acc) {
    asm volatile("{\n.reg .pred p;\nsetp.ne.b32 p, %42, 0;\n"
        "wgmma.mma_async.sync.aligned.m64n80k16.f32.bf16.bf16 "
        "{%0,%1,%2,%3,%4,%5,%6,%7,%8,%9,%10,%11,%12,%13,%14,%15,%16,%17,%18,%19,"
        "%20,%21,%22,%23,%24,%25,%26,%27,%28,%29,%30,%31,%32,%33,%34,%35,%36,%37,%38,%39}, "
        "%40, %41, p, 1, 1, 1, 0;\n}\n"
        : "+f"(d[0]), "+f"(d[1]), "+f"(d[2]), "+f"(d[3]), "+f"(d[4]), "+f"(d[5]), "+f"(d[6]), "+f"(d[7]), "+f"(d[8]), "+f"(d[9]),
          "+f"(d[10]), "+f"(d[11]), "+f"(d[12]), "+f"(d[13]), "+f"(d[14]), "+f"(d[15]), "+f"(d[16]), "+f"(d[17]), "+f"(d[18]), "+f"(d[19]),
          "+f"(d[20]), "+f"(d[21]), "+f"(d[22]), "+f"(d[23]), "+f"(d[24]), "+f"(d[25]), "+f"(d[26]), "+f"(d[27]), "+f"(d[28]), "+f"(d[29]),
          "+f"(d[30]), "+f"(d[31]), "+f"(d[32]), "+f"(d[33]), "+f"(d[34]), "+f"(d[35]), "+f"(d[36]), "+f"(d[37]), "+f"(d[38]), "+f"(d[39])
        : "l"(da), "l"(db), "r"(acc));
}

__device__ __forceinline__ void gemm_issue(float (&d)[40], uint32_t wbase, uint32_t xbase) {
    asm volatile("wgmma.fence.sync.aligned;" ::: "memory");
#pragma unroll
    for (int s = 0; s < 8; s++) {
        const uint32_t aa = wbase + s * 2048, ab = xbase + (s >> 2) * 10240 + (s & 3) * 32;
        const uint64_t da = (uint64_t)((aa & 0x3FFFF) >> 4) | ((uint64_t)64 << 16) | ((uint64_t)64 << 32) | ((uint64_t)1 << 62);
        const uint64_t db = (uint64_t)((ab & 0x3FFFF) >> 4) | ((uint64_t)1 << 16) | ((uint64_t)64 << 32) | ((uint64_t)1 << 62);
        wgmma_n80(d, da, db, s > 0);
    }
    asm volatile("wgmma.commit_group.sync.aligned;" ::: "memory");
}
__device__ __forceinline__ void gemm_wait(float (&d)[40]) {
    asm volatile("wgmma.wait_group.sync.aligned 0;" ::: "memory");
#pragma unroll
    for (int i = 0; i < 40; i++) asm volatile("" : "+f"(d[i]) :: "memory");
}
__device__ __forceinline__ void gemm_store(const float (&d)[40], float sc, uint32_t base, int w4, int lane) {
    const int mi = lane >> 3, rr = lane & 7;
    const uint32_t sa = base + (rr + 8 * (mi >> 1)) * 128 + (((2 * w4 + (mi & 1)) ^ rr) << 4);
#pragma unroll
    for (int p = 0; p < 5; p++) {
        const float* q = d + 8 * p;
        stsm4t(sa + p * 2048, pack_bf16(q[0] * sc, q[1] * sc), pack_bf16(q[2] * sc, q[3] * sc),
               pack_bf16(q[4] * sc, q[5] * sc), pack_bf16(q[6] * sc, q[7] * sc));
    }
}

struct Params {
    const int* dst;
    const int* src;
    unsigned* bar;
    uint4* xch;
    const bf16* gw;
    const bf16* e_attr;
    const char* table;
    bf16* out;
};

__global__ void __launch_bounds__(NTHR, 1)
egc_kernel(const Params p, const __grid_constant__ CUtensorMap tm_x, const __grid_constant__ CUtensorMap tm_g,
           const __grid_constant__ CUtensorMap tm_u, const __grid_constant__ CUtensorMap tm_v, const __grid_constant__ CUtensorMap tm_t) {
    extern __shared__ unsigned char smem_raw[];
    const uint32_t sb = ((uint32_t)__cvta_generic_to_shared(smem_raw) + 1023u) & ~1023u;
    const int tid = threadIdx.x, lane = tid & 31, b = blockIdx.x;
    const int w = __shfl_sync(0xffffffffu, tid >> 5, 0);
    const int wq = w >> 2, w4 = w & 3;
    const int g = lane >> 2, t = lane & 3, mi = lane >> 3, rr = lane & 7;
    TRACE(0);

    uint32_t Cf[8][4];
    auto load_cf = [&]() {
        const int krow = rr + 8 * (mi >> 1);
#pragma unroll
        for (int j = 0; j < 8; j++) {
            const int c = 2 * j + (mi & 1);
            ldsm4t(Cf[j], sb + SM_C + krow * 256 + ((c & 8) << 4) + (((c & 7) ^ rr) << 4));
#pragma unroll
            for (int q = 0; q < 4; q++) Cf[j][q] = mul_bf16x2(Cf[j][q], 0x3F003F00u);
        }
    };
    uint32_t xAf[8][2];
    float agg[8][4];
    const uint32_t ident = (g == 2 * t) ? 0x3F80u : ((g == 2 * t + 1) ? 0x3F800000u : 0u);
    const int nslot = (w < 12) ? 5 : 4;
    auto load_node_frags = [&]() {
        const int mynode = lds8(sb + SM_TNODE + w * 8 + ((rr < nslot) ? rr : 0));
#pragma unroll
        for (int jp = 0; jp < 4; jp++) {
            const int c = 4 * jp + mi;
            const uint32_t off = mynode * 128 + (((c & 7) ^ (mynode & 7)) << 4);
            uint32_t q[4];
            ldsm4t(q, sb + SM_WA + (c >> 3) * 16384 + off);
            xAf[2 * jp][0] = q[0]; xAf[2 * jp][1] = q[1]; xAf[2 * jp + 1][0] = q[2]; xAf[2 * jp + 1][1] = q[3];
            ldsm4t(q, sb + SM_X + (c >> 3) * 10240 + off);
            mma1688_z(agg[2 * jp], q[0], q[1], ident);
            mma1688_z(agg[2 * jp + 1], q[2], q[3], ident);
        }
    };
    uint32_t bar_target = 0;
    constexpr int LT = 256;
    if (wq < 2) {
        uint32_t epoch = 0;
        {
            const int r = tid >> 4, c = tid & 15;
            cp16(sb + SM_C + r * 256 + ((c & 8) << 4) + (((c & 7) ^ (r & 7)) << 4), p.gw + (256 + r) * 128 + c * 8);
            cp_commit();
        }
        if (tid == 0) {
            asm volatile("ld.relaxed.gpu.global.u32 %0, [%1];" : "=r"(epoch) : "l"(p.bar) : "memory");
            for (int i = 0; i < 9; i++) mbar_init(sb + SM_BAR + i * 8, 1);
            asm volatile("fence.mbarrier_init.release.cluster;" ::: "memory");
            const uint32_t bx = sb + SM_BAR;
            mbar_expect(bx, 20480);
#pragma unroll
            for (int i = 0; i < 8; i++) mbar_expect(bx + 8 + i * 8, 16384);
            spin(START_DELAY);
            tma_load2d(sb + SM_X, &tm_x, 0, b * NPC, bx);
            tma_load2d(sb + SM_X + 10240, &tm_x, 64, b * NPC, bx);
            tma_load2d(sb + SM_R0, &tm_g, 0, 128, bx + 8);
            tma_load2d(sb + SM_R0 + 16384, &tm_g, 64, 128, bx + 16);
            tma_load2d(sb + SM_R0 + 2 * 16384, &tm_v, 0, 0, bx + 24);
            tma_load2d(sb + SM_R0 + 3 * 16384, &tm_v, 64, 0, bx + 32);
        }
        cp_wait<0>();
        asm volatile("bar.sync 6, 256;" ::: "memory");
        asm volatile("bar.arrive 8, 512;" ::: "memory");
        TRACE(1);
        load_cf();
        float d[40];
        const uint32_t xt = sb + SM_X;
        const bool elect = (w4 == 0 && lane == 0);
        mbar_wait(sb + SM_BAR, 0);
#pragma unroll 1
        for (int r = 0; r < 4; r++) {
            const uint32_t wt = sb + ((r < 2) ? SM_R0 + r * 32768 : ((r == 2) ? SM_WA : SM_WU)) + wq * 16384;
            mbar_wait(sb + SM_BAR + 8 + (2 * r + wq) * 8, 0);
            TRACE(2 + 2 * r);
            gemm_issue(d, wt, xt);
            if (r == 0 && tid == 0) {
#pragma unroll
                for (int i = 0; i < 2; i++) {
                    tma_load2d(sb + SM_WA + i * 16384, &tm_g, i * 64, 0, sb + SM_BAR + 8 + (4 + i) * 8);
                    tma_load2d(sb + SM_WU + i * 16384, &tm_u, i * 64, 0, sb + SM_BAR + 8 + (6 + i) * 8);
                }
            }
            if (r == 2) {
                asm volatile("bar.sync 4, 512;" ::: "memory");
                if (elect) {
                    asm volatile("cp.async.bulk.wait_group 0;" ::: "memory");
                    asm volatile("fence.proxy.async.global;" ::: "memory");
                    asm volatile("red.relaxed.gpu.global.add.u32 [%0], 1;" :: "l"(p.bar) : "memory");
                }
            }
            if (r == 3 && tid == 0) {
                const int e0 = b * ECH, ne = min(ECH, EE - e0);
                asm volatile("cp.async.bulk.prefetch.L2.global [%0], %1;" :: "l"(p.e_attr + (size_t)e0 * 16), "r"(ne * 32) : "memory");
            }
            __syncwarp();
            gemm_wait(d);
            if (r < 3) wg_bar(1 + wq); else asm volatile("bar.sync 6, 256;" ::: "memory");
            gemm_store(d, (r == 1) ? 0.25f : 0.5f, (r < 3) ? wt : xt + wq * 10240, w4, lane);
            if (r < 2) {
                asm volatile("fence.proxy.async.shared::cta;" ::: "memory");
                wg_bar(1 + wq);
                if (elect) {
                    tma_store2d(&tm_t, (2 * r + wq) * 64, b * NPC, wt);
                    asm volatile("cp.async.bulk.commit_group;" ::: "memory");
                }
                __syncwarp();
            }
            TRACE(3 + 2 * r);
        }

        bar_target = (epoch / (2 * NCTA) + 1) * (2 * NCTA);
        TRACE(9);
    } else {
        const int lt = tid - LT;
        int ed[5], es[5];
        uint32_t epoch;
#pragma unroll
        for (int m = 0; m < 5; m++) {
            const int k = lt + m * LT, e = b * ECH + k;
            ed[m] = ((k < ECH) && (e < EE)) ? __ldg(p.dst + e) : -1;
        }
#pragma unroll
        for (int m = 0; m < 5; m++) {
            const int k = lt + m * LT, e = b * ECH + k;
            es[m] = ((k < ECH) && (e < EE)) ? __ldg(p.src + e) : 0;
        }
        asm volatile("ld.relaxed.gpu.global.u32 %0, [%1];" : "=r"(epoch) : "l"(p.bar) : "memory");
        if (lt < 136) sts32(sb + SM_HIST + lt * 4, 0);
        if (lt < 128) { sts32(sb + SM_KEYS + lt * 4, 0); sts32(sb + SM_TDEG + lt * 4, 0); }
        if (lt < 64) sts32(sb + SM_DBIN + lt * 4, 0);
        if (lt == 0) sts32(sb + SM_FLAG, 0);
        lt_bar();
        TRACE(24);
        {
            uint32_t jj[5], rk[5];
#pragma unroll
            for (int m = 0; m < 5; m++) {
                jj[m] = (ed[m] >= 0) ? (((uint32_t)ed[m] * 55189u) >> 22) : (132 + (lane & 3));
                rk[m] = atoms_add(sb + SM_HIST + jj[m] * 4, 1);
            }
#pragma unroll
            for (int m = 0; m < 5; m++) {
                const uint32_t loc = (uint32_t)ed[m] - jj[m] * NPC;
                const uint32_t q = (rk[m] * 43691u) >> 17;
                const uint32_t off = jj[m] * (PIECES * 16) + q * 16 + (rk[m] - 3 * q + 1) * 4;
                sts32(sb + SM_S + ((ed[m] >= 0 && rk[m] < XCAP) ? off : NCTA * PIECES * 16 + lane * 4),
                      (uint32_t)es[m] | (loc << 14) | ((uint32_t)(lt + m * LT) << 21));
            }
        }
        const uint32_t bar_q = epoch / (2 * NCTA);
        epoch = (bar_q + 1) & 0xFFFFFF;
        TRACE(25);
        lt_bar();
        {
            uint4 v[6]; uint32_t c[6];
#pragma unroll
            for (int m = 0; m < 6; m++) {
                const int pc = min(lt + m * LT, NCTA * PIECES - 1);
                v[m] = lds128(sb + SM_S + pc * 16);
                c[m] = lds32(sb + SM_HIST + ((pc * 6554) >> 16) * 4);
            }
#pragma unroll
            for (int m = 0; m < 6; m++) {
                const int pc = lt + m * LT;
                const int j = (pc * 6554) >> 16, q = pc - j * PIECES;
                if ((m < 5 || pc < NCTA * PIECES) && (q < 4 || c[m] > 3 * (q & ~1) || b >= 128)) {
                    v[m].x = (epoch << 8) | min(c[m], 255u);
                    st_piece(p.xch + (((j * (PIECES / 2) + (q >> 1)) * NCTA + b) * 2 + (q & 1)), v[m]);
                }
            }
        }
        TRACE(46);
        asm volatile("bar.arrive 4, 512;" ::: "memory");
        lt_bar();
        if (lt == 0) asm volatile("red.relaxed.gpu.global.add.u32 [%0], 1;" :: "l"(p.bar + 1) : "memory");
        asm volatile("bar.sync 8, 512;" ::: "memory");
        load_cf();
        if (lt == 0) {
            uint32_t v; int it = 0;
            const uint32_t target = bar_q * NCTA + NCTA / 2;
            do { asm volatile("ld.relaxed.gpu.global.u32 %0, [%1];" : "=r"(v) : "l"(p.bar + 1) : "memory"); }
            while ((int)(v - target) < 0 && ++it < SPIN_LIMIT);
        }
        lt_bar();
        TRACE(26);
        uint4 pv[6];
        const int pi5 = 128 + ((lt >> 1) & 3), pq5 = 2 * (lt >> 3) + (lt & 1);
        const uint4* px0 = p.xch + b * (NCTA * PIECES) + lt;
        const uint4* px5 = p.xch + b * (NCTA * PIECES) + (lt >> 3) * (2 * NCTA) + 256 + (lt & 7);
        const uint32_t tg = epoch << 8;
        auto fetch = [&](const uint4* a) {
            uint4 v = ld_piece(a);
            int it = 0;
            while (((v.x ^ tg) >> 8) && ++it < SPIN_LIMIT) { __nanosleep(100); v = ld_piece(a); }
            return v;
        };
        pv[0] = ld_piece(px0);
        pv[1] = ld_piece(px0 + 2 * NCTA);
        pv[5] = (lt < 4 * PIECES) ? ld_piece(px5) : make_uint4(tg, 0, 0, 0);
        for (int it = 0; (((pv[0].x ^ tg) | (pv[1].x ^ tg) | (pv[5].x ^ tg)) >> 8) && it < SPIN_LIMIT; it++) {
            __nanosleep(100);
            if ((pv[0].x ^ tg) >> 8) pv[0] = ld_piece(px0);
            if ((pv[1].x ^ tg) >> 8) pv[1] = ld_piece(px0 + 2 * NCTA);
            if ((pv[5].x ^ tg) >> 8) pv[5] = ld_piece(px5);
        }
        const int cnt = pv[0].x & 255, cnt5 = pv[5].x & 255;
#pragma unroll
        for (int m = 2; m < 5; m++) pv[m] = (cnt > 6 * m) ? ld_piece(px0 + m * (2 * NCTA)) : make_uint4(tg, 0, 0, 0);
        if (cnt > XCAP || cnt5 > XCAP) sts32(sb + SM_FLAG, 1);
        TRACE(27);
        const uint32_t dmy = (96 + lane) * 4;
        uint32_t ao[9], rk[9];
        auto count = [&](int m, int o) {
            const int nv = (m < 5) ? cnt - 3 * (2 * m + (lt & 1)) : cnt5 - 3 * pq5;
#pragma unroll
            for (int s = 0; s < 3; s++) {
                const uint32_t pl = (s == 0) ? pv[m].y : ((s == 1) ? pv[m].z : pv[m].w);
                ao[o + s] = (nv > s) ? ((pl >> 12) & 0x1FC) : dmy;
                rk[o + s] = atoms_add(sb + SM_KEYS + ao[o + s], 1);
            }
        };
        auto put = [&](int m, int o) {
            const uint32_t e0s = (uint32_t)(((m < 5) ? (lt >> 1) : pi5) * ECH) << 14;
#pragma unroll
            for (int s = 0; s < 3; s++) {
                const uint32_t pl = (s == 0) ? pv[m].y : ((s == 1) ? pv[m].z : pv[m].w);
                const bool ok = ao[o + s] < 96 * 4 && rk[o + s] < NCAP;
                sts32(sb + SM_NL + (ok ? ao[o + s] * NCAP + rk[o + s] * 4 : NPC * NCAP * 4 + lane * 4), (pl & 0x3FFF) + ((pl >> 21) << 14) + e0s);
            }
        };
        count(0, 0);
        count(1, 3);
        const bool has5 = lt < 64;
        if (has5) count(5, 6);
        put(0, 0);
        put(1, 3);
        if (has5) put(5, 6);
        if (((pv[2].x ^ tg) | (pv[3].x ^ tg) | (pv[4].x ^ tg)) >> 8) {
#pragma unroll
            for (int m = 2; m < 5; m++) if (cnt > 6 * m) pv[m] = fetch(px0 + m * (2 * NCTA));
        }
#pragma unroll
        for (int m = 2; m < 5; m++) {
            if (__any_sync(0xffffffffu, cnt > 6 * m)) { count(m, 0); put(m, 0); }
        }
        TRACE(28);
        lt_bar();
        if (lt < 96) {
            const uint32_t deg = (lt < NPC) ? lds32(sb + SM_KEYS + lt * 4) : 0;
            const uint32_t bin = 63 - min(deg, 63u);
            const uint32_t r0 = atoms_add_p(lt < NPC, sb + SM_DBIN + bin * 4, 1);
            if (deg > NCAP) sts32(sb + SM_FLAG, 1);
            asm volatile("bar.sync 5, 96;" ::: "memory");
            const uint2 c2 = lds64(sb + SM_DBIN + lane * 8);
            uint32_t inc = c2.x + c2.y;
#pragma unroll
            for (int o = 1; o < 32; o <<= 1) { const uint32_t u = __shfl_up_sync(0xffffffffu, inc, o); if (lane >= o) inc += u; }
            const uint32_t ex = inc - c2.x - c2.y;
            const uint32_t pe = __shfl_sync(0xffffffffu, ex, bin >> 1), p0 = __shfl_sync(0xffffffffu, c2.x, bin >> 1);
            const int rank = pe + ((bin & 1) ? p0 : 0) + r0;
            const int k = rank >> 4, pos = rank & 15;
            const int tile = (k == 4) ? 11 - pos : ((pos < 4) ? 12 + ((k & 1) ? 3 - pos : pos) : ((k < 3) ? pos - 4 : 15 - pos));
            if (lt < NPC) {
                sts32(sb + SM_TDEG + (tile * 8 + k) * 4, deg);
                sts8(sb + SM_TNODE + tile * 8 + k, lt);
            }
        }
        TRACE(29);
        TRACE(30);
    }
    TRACE(31);
    __syncthreads();
    TRACE(32);
    bool slow = lds32(sb + SM_FLAG) != 0;

    constexpr uint32_t RD = SM_R1 - SM_R0;
    const uint32_t ring0 = sb + SM_R0 + w * STAGE;
    const char* tab_l = p.table + lane * 16;
    asm volatile("" : "+l"(tab_l));
    const char* e_l = (const char*)p.e_attr + (mi & 1) * 16;
    asm volatile("" : "+l"(e_l));
    const uint32_t cpo = lane * 16;
    const uint32_t elo = 4096 + rr * 32 + (((mi & 1) ^ ((rr >> 2) & 1)) << 4);
    const uint32_t lsrc = sb + SM_LSE + w * TCAP * 4, lid = sb + SM_LID + w * TCAP;
    const uint32_t lec = rr * 4;

    auto issue_full = [&](uint32_t lp, uint32_t dl) {
        const uint4 s0 = lds128(lp), s1 = lds128(lp + 16);
        const uint32_t eo = lds32(lp + lec);
        const uint32_t sv[8] = {s0.x, s0.y, s0.z, s0.w, s1.x, s1.y, s1.z, s1.w};
#pragma unroll
        for (int j = 0; j < 8; j++) cp16(ring0 + dl + (cpo ^ (j << 4)) + j * 512, madw(sv[j] & 0x3FFF, 512, tab_l));
        cp16(ring0 + dl + elo, madw(eo >> 14, 32, e_l));
    };
    auto issue0 = [&]() {
        const int cnt = lds32(sb + SM_TCNT + w * 4), nit = (cnt + 7) >> 3;
        if (nit > 0) {
            const int pad = nit * 8 - cnt;
            const uint4 s0 = lds128(lsrc), s1 = lds128(lsrc + 16);
            const uint32_t eo = lds32(lsrc + lec);
            const uint32_t sv[8] = {s0.x, s0.y, s0.z, s0.w, s1.x, s1.y, s1.z, s1.w};
#pragma unroll
            for (int j = 0; j < 8; j++) cp16z(ring0 + (cpo ^ (j << 4)) + j * 512, madw(sv[j] & 0x3FFF, 512, tab_l), (j >= pad) ? 16 : 0);
            cp16z(ring0 + elo, madw(eo >> 14, 32, e_l), (rr >= pad) ? 16 : 0);
        }
        cp_commit();
    };
    auto issue1 = [&]() {
        if ((int)lds32(sb + SM_TCNT + w * 4) > 8) issue_full(lsrc + 32, RD);
        cp_commit();
    };
    uint32_t bar_v = 0;
    bool over = false;
    if (tid == 0) asm volatile("ld.relaxed.gpu.global.u32 %0, [%1];" : "=r"(bar_v) : "l"(p.bar) : "memory");
    if (!slow) {
        const uint2 tn = lds64(sb + SM_TNODE + w * 8);
        const uint4 dg = lds128(sb + SM_TDEG + w * 32);
        const uint32_t p1 = dg.x, p2 = p1 + dg.y, p3 = p2 + dg.z, p4 = p3 + dg.w, tot = p4 + lds32(sb + SM_TDEG + w * 32 + 16);
        const uint32_t pad = (0u - tot) & 7u;
        if (lane == 0) sts32(sb + SM_TCNT + w * 4, tot);
        over = tot + pad > TCAP;
        uint32_t wd[TCAP / 32], sl[TCAP / 32];
#pragma unroll
        for (int r = 0; r < TCAP / 32; r++) {
            const uint32_t q = lane + 32 * r - pad;
            sl[r] = (q >= p1) + (q >= p2) + (q >= p3) + (q >= p4);
            const uint32_t pre = (q >= p4) ? p4 : ((q >= p3) ? p3 : ((q >= p2) ? p2 : ((q >= p1) ? p1 : 0)));
            const uint32_t node = prmt(tn.x, tn.y, sl[r]) & 0xFF;
            wd[r] = lds32(sb + SM_NL + ((q < tot) ? (node * NCAP + q - pre) * 4 : 0));
        }
#pragma unroll
        for (int r = 0; r < TCAP / 32; r++) {
            const uint32_t q = lane + 32 * r - pad;
            sts32(lsrc + (lane + 32 * r) * 4, (q < tot) ? wd[r] : 0);
            sts8(lid + lane + 32 * r, (q < tot) ? sl[r] * 16 : 0x7F);
        }
    }
    TRACE(10);
    if (tid == 0) {
        int it = 0;
        while ((int)(bar_v - bar_target) < 0 && ++it < SPIN_LIMIT)
            asm volatile("ld.relaxed.gpu.global.u32 %0, [%1];" : "=r"(bar_v) : "l"(p.bar) : "memory");
    }
    slow = __syncthreads_or(slow || over);
    TRACE(11);
    if (!slow) {
        issue0();
        issue1();
    } else {
        if (tid < NPC) sts8(sb + SM_TNODE + (tid & 15) * 8 + (tid >> 4), tid);
        __syncthreads();
    }
    TRACE(33);
    load_node_frags();
    TRACE(34);

    const uint32_t ldo = rr * 512 + ((mi ^ rr) << 4);
    const uint32_t sel = (g | ((8 | g) << 4) | (g << 8) | ((8 | g) << 12)) |
                         (((2 * t) | ((8 | (2 * t)) << 4) | ((2 * t + 1) << 8) | ((8 | (2 * t + 1)) << 12)) << 16);
    const uint32_t gg = (g * 16) | ((g * 16) << 16);
    const uint32_t tt = (t * 32) | ((t * 32 + 16) << 16);

    auto compute = [&](uint32_t st, uint32_t idp) {
        uint32_t eb[2];
        ldsm2(eb, st + elo);
        const uint2 iw = lds64(idp);
        const uint32_t sx = seteq_bf16x2(prmt(iw.x, iw.y, sel), tt);
        const uint32_t sa = seteq_bf16x2(prmt(iw.x, iw.y, sel >> 16), gg);
#pragma unroll
        for (int jj = 0; jj < 4; jj++) {
            uint32_t xb[4], hv[4];
            const uint32_t la = st + (ldo ^ ((jj & 1) << 6)) + (jj >> 1) * 128;
            ldsm4(xb, la);
            ldsm4t(hv, la + 256);
#pragma unroll
            for (int u = 0; u < 2; u++) {
                const int j = 2 * jj + u;
                float d[4];
                mma16816_z(d, Cf[j][0], Cf[j][1], Cf[j][2], Cf[j][3], eb[0], eb[1]);
                mma1688(d, xAf[j][0], xAf[j][1], sx);
                mma16816(d, ident, 0u, 0u, ident, xb[2 * u], xb[2 * u + 1]);
                const uint32_t m0 = fma_bf16x2(pack_bf16(tanh_ap(d[0]), tanh_ap(d[1])), hv[2 * u], hv[2 * u]);
                const uint32_t m1 = fma_bf16x2(pack_bf16(tanh_ap(d[2]), tanh_ap(d[3])), hv[2 * u + 1], hv[2 * u + 1]);
                mma1688(agg[j], m0, m1, sa);
            }
        }
    };

    const int nseg = slow ? NSEG : 1;
#pragma unroll 1
    for (int seg = 0; seg < nseg; seg++) {
        if (slow) {
            __syncthreads();
            if (tid < 16) sts32(sb + SM_TCNT + tid * 4, 0);
            __syncthreads();
            const int e = seg * TCAP + tid;
            int loc = -1; uint32_t r = 0;
            if (tid < TCAP && e < EE) {
                const int dd = __ldg(p.dst + e) - b * NPC;
                if (dd >= 0 && dd < NPC) { loc = dd; r = atoms_add(sb + SM_TCNT + (loc & 15) * 4, 1); }
            }
            __syncthreads();
            if (loc >= 0) {
                const uint32_t tile = loc & 15, tot = lds32(sb + SM_TCNT + tile * 4);
                const uint32_t pos = tile * TCAP + ((0u - tot) & 7u) + r;
                sts32(sb + SM_LSE + pos * 4, (uint32_t)__ldg(p.src + e) | ((uint32_t)e << 14));
                sts8(sb + SM_LID + pos, (loc >> 4) << 4);
            }
            const int pad = (0 - (int)lds32(sb + SM_TCNT + w * 4)) & 7;
            if (lane < pad) { sts8(sb + SM_LID + w * TCAP + lane, 0x7F); sts32(sb + SM_LSE + (w * TCAP + lane) * 4, 0); }
            __syncthreads();
            issue0();
            issue1();
        }
        const int nit = __shfl_sync(0xffffffffu, ((int)lds32(sb + SM_TCNT + w * 4) + 7) >> 3, 0);
        uint32_t st = ring0, so = ring0 + RD, lp = lsrc + 32, idp = lid;
        const uint32_t lend = lsrc + nit * 32;
        constexpr int AVG_NIT = (EE + NCTA * 128 - 1) / (NCTA * 128);
        constexpr int HEAVY = EE / NN * NPC * 207 / 200;
        const int ctot = __reduce_add_sync(0xffffffffu, (lane < 16) ? (int)lds32(sb + SM_TCNT + lane * 4) : 0);
        if (nit <= AVG_NIT && ctot <= HEAVY) {
#pragma unroll 1
            for (; lp <= lend; lp += 32, idp += 8) {
                if (idp == lid) cp_wait<1>(); else cp_wait<0>();
                __syncwarp();
                if (idp != lid && lp < lend) issue_full(lp, so - ring0);
                cp_commit();
                compute(st, idp);
                const uint32_t tmp = st; st = so; so = tmp;
            }
        } else {
#pragma unroll 1
            for (; lp <= lend; lp += 32, idp += 8) {
                cp_wait<1>();
                __syncwarp();
                compute(st, idp);
                __syncwarp();
                if (lp + 32 < lend) issue_full(lp + 32, st - ring0);
                cp_commit();
                const uint32_t tmp = st; st = so; so = tmp;
            }
        }
        cp_wait<0>();
        __syncwarp();
    }
    TRACE(35);

    {
        uint32_t o[8][2];
#pragma unroll
        for (int j = 0; j < 8; j++) {
            float v[4];
#pragma unroll
            for (int q = 0; q < 4; q++) { const float h = agg[j][q]; v[q] = fmaf(h, tanh_ap(h), h); }
            o[j][0] = pack_bf16(v[0], v[1]); o[j][1] = pack_bf16(v[2], v[3]);
        }
#pragma unroll
        for (int jp = 0; jp < 4; jp++) {
            const int c = 4 * jp + mi;
            stsm4t(ring0 + rr * 256 + ((c & 8) << 4) + (((c & 7) ^ rr) << 4), o[2 * jp][0], o[2 * jp][1], o[2 * jp + 1][0], o[2 * jp + 1][1]);
        }
        __syncwarp();
#pragma unroll
        for (int i = 0; i < 3; i++) {
            const int idx = lane + 32 * i, row = idx >> 4, c = idx & 15;
            const int nd = b * NPC + (int)lds8(sb + SM_TNODE + w * 8 + (row & 7));
            if (row < nslot && nd < NN) {
                const uint4 v = lds128(ring0 + row * 256 + ((c & 8) << 4) + (((c & 7) ^ row) << 4));
                *(uint4*)((char*)p.out + (size_t)nd * 256 + c * 16) = v;
            }
        }
    }
    TRACE(36);
}

__device__ __align__(16) bf16 g_fb_xa[NN * 128];
__device__ __align__(16) float g_fb_h[NN * 128];

__global__ void fb_node_kernel(const bf16* x, const bf16* uw, const bf16* vw, const bf16* gw, bf16* table) {
    __shared__ float xs[128];
    const int n = blockIdx.x, f = threadIdx.x;
    xs[f] = __bfloat162float(x[n * 128 + f]);
    __syncthreads();
    float a = 0.f, bb = 0.f, v = 0.f, u = 0.f;
    for (int k = 0; k < 128; k++) {
        const float xv = xs[k];
        a += xv * __bfloat162float(gw[k * 128 + f]);
        bb += xv * __bfloat162float(gw[(128 + k) * 128 + f]);
        v += xv * __bfloat162float(vw[k * 128 + f]);
        u += xv * __bfloat162float(uw[k * 128 + f]);
    }
    table[n * 256 + f] = __float2bfloat16(0.5f * bb);
    table[n * 256 + 128 + f] = __float2bfloat16(0.25f * v);
    g_fb_xa[n * 128 + f] = __float2bfloat16(0.5f * a);
    g_fb_h[n * 128 + f] = 0.5f * u;
}
__global__ void fb_edge_kernel(const bf16* e_attr, const int* src, const int* dst, const bf16* gw, const bf16* table) {
    const int e = blockIdx.x, f = threadIdx.x, s = src[e], d = dst[e];
    float z = 0.f;
    for (int k = 0; k < 16; k++) z += __bfloat162float(e_attr[e * 16 + k]) * __bfloat162float(gw[(256 + k) * 128 + f]);
    z = 0.5f * z + __bfloat162float(g_fb_xa[d * 128 + f]) + __bfloat162float(table[s * 256 + f]);
    const float hv = __bfloat162float(table[s * 256 + 128 + f]);
    atomicAdd(&g_fb_h[d * 128 + f], fmaf(hv, tanhf(z), hv));
}
__global__ void fb_out_kernel(bf16* out) {
    const int i = blockIdx.x * 128 + threadIdx.x;
    const float h = g_fb_h[i];
    out[i] = __float2bfloat16(fmaf(h, tanhf(h), h));
}

typedef CUresult (*EncodeFn)(CUtensorMap*, CUtensorMapDataType, cuuint32_t, void*, const cuuint64_t*, const cuuint64_t*,
                             const cuuint32_t*, const cuuint32_t*, CUtensorMapInterleave, CUtensorMapSwizzle,
                             CUtensorMapL2promotion, CUtensorMapFloatOOBfill);

static void make_map(EncodeFn enc, CUtensorMap* tm, const void* base, int rows, int cols, int box_rows) {
    cuuint64_t dims[2] = {(cuuint64_t)cols, (cuuint64_t)rows};
    cuuint64_t strides[1] = {(cuuint64_t)cols * 2};
    cuuint32_t box[2] = {64, (cuuint32_t)box_rows};
    cuuint32_t es[2] = {1, 1};
    enc(tm, CU_TENSOR_MAP_DATA_TYPE_BFLOAT16, 2, (void*)base, dims, strides, box, es, CU_TENSOR_MAP_INTERLEAVE_NONE,
        CU_TENSOR_MAP_SWIZZLE_128B, CU_TENSOR_MAP_L2_PROMOTION_NONE, CU_TENSOR_MAP_FLOAT_OOB_FILL_NONE);
}

}

extern "C" void kernel_launch(void* const* d_in, const int* in_sizes, int n_in, void* d_out, int out_size) {
    using namespace egc;
    (void)in_sizes; (void)n_in; (void)out_size;
    static EncodeFn enc = nullptr;
    static void* table = nullptr;
    static void* xch = nullptr;
    static void* bar = nullptr;
    static bool persistent = false;
    if (!enc) {
        void* fn = nullptr;
        cudaDriverEntryPointQueryResult qr;
        cudaGetDriverEntryPoint("cuTensorMapEncodeTiled", &fn, cudaEnableDefault, &qr);
        enc = (EncodeFn)fn;
        cudaGetSymbolAddress(&table, g_table);
        cudaGetSymbolAddress(&xch, g_xch);
        cudaGetSymbolAddress(&bar, g_bar);
        cudaFuncSetAttribute(egc_kernel, cudaFuncAttributeMaxDynamicSharedMemorySize, SMEM_BYTES);
        int dev = 0, sms = 0, per_sm = 0;
        cudaGetDevice(&dev);
        cudaDeviceGetAttribute(&sms, cudaDevAttrMultiProcessorCount, dev);
        cudaOccupancyMaxActiveBlocksPerMultiprocessor(&per_sm, egc_kernel, NTHR, SMEM_BYTES);
        persistent = enc != nullptr && sms * per_sm >= NCTA;
    }
    if (!persistent) {
        const bf16* x = (const bf16*)d_in[0];
        fb_node_kernel<<<NN, 128, 0, cudaStreamPerThread>>>(x, (const bf16*)d_in[4], (const bf16*)d_in[5], (const bf16*)d_in[6], (bf16*)table);
        fb_edge_kernel<<<EE, 128, 0, cudaStreamPerThread>>>((const bf16*)d_in[1], (const int*)d_in[2], (const int*)d_in[3], (const bf16*)d_in[6], (const bf16*)table);
        fb_out_kernel<<<NN, 128, 0, cudaStreamPerThread>>>((bf16*)d_out);
        return;
    }
    CUtensorMap tm_x, tm_g, tm_u, tm_v, tm_t;
    make_map(enc, &tm_x, d_in[0], NN, 128, 80);
    make_map(enc, &tm_u, d_in[4], 128, 128, 128);
    make_map(enc, &tm_v, d_in[5], 128, 128, 128);
    make_map(enc, &tm_g, d_in[6], 272, 128, 128);
    make_map(enc, &tm_t, table, NN, 256, NPC);
    Params p;
    p.e_attr = (const bf16*)d_in[1];
    p.src = (const int*)d_in[2];
    p.dst = (const int*)d_in[3];
    p.gw = (const bf16*)d_in[6];
    p.out = (bf16*)d_out;
    p.bar = (unsigned*)bar;
    p.xch = (uint4*)xch;
    p.table = (const char*)table;
    egc_kernel<<<NCTA, NTHR, SMEM_BYTES, cudaStreamPerThread>>>(p, tm_x, tm_g, tm_u, tm_v, tm_t);
}
```

```cpp
#include <cuda_runtime.h>
#include <cuda_bf16.h>
#include <cuda.h>
#include <stdint.h>
#include <type_traits>

namespace egc {

typedef __nv_bfloat16 bf16;

constexpr int NN = 10000, EE = 160000;
constexpr int NCTA = 132, NPC = 76, ECH = 1216, NTHR = 512;
constexpr int PIECES = 10, XCAP = 3 * PIECES;
constexpr int TCAP = 96;
constexpr int NSEG = (EE + TCAP - 1) / TCAP;
constexpr int SPIN_LIMIT = 1 << 20;
constexpr uint32_t START_DELAY = 420;

constexpr int STAGE = 4352;
constexpr int SM_R0 = 0;
constexpr int SM_R1 = 16 * STAGE;
constexpr int SM_S = SM_R1;
constexpr int SM_WU = SM_R1 + 8 * STAGE;
constexpr int SM_WA = SM_R1 + 16 * STAGE;
constexpr int SM_X = SM_WA + 32768;
constexpr int SM_C = SM_X + 20480;
constexpr int SM_LSE = SM_C + 4096;
constexpr int SM_LID = SM_LSE + 6144 + 128;
constexpr int SM_HIST = SM_LID + 1536 + 32;
constexpr int SM_KEYS = SM_HIST + 544;
constexpr int SM_CURS = SM_KEYS + 512;
constexpr int SM_DBIN = SM_CURS + 512;
constexpr int SM_TDEG = SM_DBIN + 256;
constexpr int SM_TNODE = SM_TDEG + 512;
constexpr int SM_TCNT = SM_TNODE + 128;
constexpr int SM_FLAG = SM_TCNT + 64;
constexpr int NCAP = 40;
constexpr int SM_NL = SM_FLAG + 16;
constexpr int SM_BAR = SM_NL + NPC * NCAP * 4 + 128;
constexpr int SM_TRACE = SM_BAR + 9 * 8 + 8;
constexpr int SM_END = SM_TRACE + 2 * 48 * 4;
constexpr int SMEM_BYTES = SM_END + 1024;

__device__ __align__(1024) uint4 g_table[NN * 32];
__device__ __align__(1024) uint4 g_xch[NCTA * NCTA * PIECES];
__device__ __align__(128) unsigned g_bar[32];
#define TRACE(i) do {} while (0)

__device__ __forceinline__ void mma16816(float* d, uint32_t a0, uint32_t a1, uint32_t a2, uint32_t a3, uint32_t b0, uint32_t b1) {
    asm("mma.sync.aligned.m16n8k16.row.col.f32.bf16.bf16.f32 {%0,%1,%2,%3}, {%4,%5,%6,%7}, {%8,%9}, {%0,%1,%2,%3};"
        : "+f"(d[0]), "+f"(d[1]), "+f"(d[2]), "+f"(d[3]) : "r"(a0), "r"(a1), "r"(a2), "r"(a3), "r"(b0), "r"(b1));
}
__device__ __forceinline__ void mma16816_z(float* d, uint32_t a0, uint32_t a1, uint32_t a2, uint32_t a3, uint32_t b0, uint32_t b1) {
    asm("mma.sync.aligned.m16n8k16.row.col.f32.bf16.bf16.f32 {%0,%1,%2,%3}, {%4,%5,%6,%7}, {%8,%9}, {%10,%10,%10,%10};"
        : "=f"(d[0]), "=f"(d[1]), "=f"(d[2]), "=f"(d[3]) : "r"(a0), "r"(a1), "r"(a2), "r"(a3), "r"(b0), "r"(b1), "f"(0.f));
}
__device__ __forceinline__ void mma1688(float* d, uint32_t a0, uint32_t a1, uint32_t b0) {
    asm("mma.sync.aligned.m16n8k8.row.col.f32.bf16.bf16.f32 {%0,%1,%2,%3}, {%4,%5}, {%6}, {%0,%1,%2,%3};"
        : "+f"(d[0]), "+f"(d[1]), "+f"(d[2]), "+f"(d[3]) : "r"(a0), "r"(a1), "r"(b0));
}
__device__ __forceinline__ void mma1688_z(float* d, uint32_t a0, uint32_t a1, uint32_t b0) {
    asm("mma.sync.aligned.m16n8k8.row.col.f32.bf16.bf16.f32 {%0,%1,%2,%3}, {%4,%5}, {%6}, {%7,%7,%7,%7};"
        : "=f"(d[0]), "=f"(d[1]), "=f"(d[2]), "=f"(d[3]) : "r"(a0), "r"(a1), "r"(b0), "f"(0.f));
}
__device__ __forceinline__ void ldsm4(uint32_t* r, uint32_t addr) {
    asm volatile("ldmatrix.sync.aligned.m8n8.x4.shared.b16 {%0,%1,%2,%3}, [%4];" : "=r"(r[0]), "=r"(r[1]), "=r"(r[2]), "=r"(r[3]) : "r"(addr) : "memory");
}
__device__ __forceinline__ void ldsm4t(uint32_t* r, uint32_t addr) {
    asm volatile("ldmatrix.sync.aligned.m8n8.x4.trans.shared.b16 {%0,%1,%2,%3}, [%4];" : "=r"(r[0]), "=r"(r[1]), "=r"(r[2]), "=r"(r[3]) : "r"(addr) : "memory");
}
__device__ __forceinline__ void ldsm2(uint32_t* r, uint32_t addr) {
    asm volatile("ldmatrix.sync.aligned.m8n8.x2.shared.b16 {%0,%1}, [%2];" : "=r"(r[0]), "=r"(r[1]) : "r"(addr) : "memory");
}
__device__ __forceinline__ void stsm4t(uint32_t addr, uint32_t r0, uint32_t r1, uint32_t r2, uint32_t r3) {
    asm volatile("stmatrix.sync.aligned.m8n8.x4.trans.shared.b16 [%0], {%1,%2,%3,%4};" :: "r"(addr), "r"(r0), "r"(r1), "r"(r2), "r"(r3) : "memory");
}
__device__ __forceinline__ float tanh_ap(float x) { float r; asm("tanh.approx.f32 %0, %1;" : "=f"(r) : "f"(x)); return r; }
__device__ __forceinline__ uint32_t pack_bf16(float lo, float hi) { uint32_t r; asm("cvt.rn.bf16x2.f32 %0, %1, %2;" : "=r"(r) : "f"(hi), "f"(lo)); return r; }
__device__ __forceinline__ uint32_t fma_bf16x2(uint32_t a, uint32_t b, uint32_t c) { uint32_t r; asm("fma.rn.bf16x2 %0, %1, %2, %3;" : "=r"(r) : "r"(a), "r"(b), "r"(c)); return r; }
__device__ __forceinline__ uint32_t mul_bf16x2(uint32_t a, uint32_t b) { uint32_t r; asm("mul.rn.bf16x2 %0, %1, %2;" : "=r"(r) : "r"(a), "r"(b)); return r; }
__device__ __forceinline__ uint32_t seteq_bf16x2(uint32_t a, uint32_t b) { uint32_t r; asm("set.eq.bf16x2.bf16x2 %0, %1, %2;" : "=r"(r) : "r"(a), "r"(b)); return r; }
__device__ __forceinline__ uint32_t prmt(uint32_t a, uint32_t b, uint32_t s) { uint32_t r; asm("prmt.b32 %0, %1, %2, %3;" : "=r"(r) : "r"(a), "r"(b), "r"(s)); return r; }
__device__ __forceinline__ uint32_t shl_clamp(uint32_t a, uint32_t s) { uint32_t r; asm("shl.b32 %0, %1, %2;" : "=r"(r) : "r"(a), "r"(s)); return r; }
__device__ __forceinline__ void cp16(uint32_t dst, const void* src) { asm volatile("cp.async.cg.shared.global [%0], [%1], 16;" :: "r"(dst), "l"(src) : "memory"); }
__device__ __forceinline__ void cp16z(uint32_t dst, const void* src, uint32_t sz) { asm volatile("cp.async.cg.shared.global [%0], [%1], 16, %2;" :: "r"(dst), "l"(src), "r"(sz) : "memory"); }
__device__ __forceinline__ const void* madw(uint32_t a, uint32_t m, const void* base) {
    const void* r; asm("mad.wide.u32 %0, %1, %2, %3;" : "=l"(r) : "r"(a), "r"(m), "l"(base)); return r;
}
__device__ __forceinline__ void cp16_p(bool p, uint32_t dst, const void* src) {
    asm volatile("{\n.reg .pred p;\nsetp.ne.u32 p, %2, 0;\n@p cp.async.cg.shared.global [%0], [%1], 16;\n}" :: "r"(dst), "l"(src), "r"((uint32_t)p) : "memory");
}
__device__ __forceinline__ void cp_commit() { asm volatile("cp.async.commit_group;" ::: "memory"); }
template <int N> __device__ __forceinline__ void cp_wait() { asm volatile("cp.async.wait_group %0;" :: "n"(N) : "memory"); }
__device__ __forceinline__ uint4 lds128(uint32_t a) { uint4 v; asm volatile("ld.shared.v4.u32 {%0,%1,%2,%3}, [%4];" : "=r"(v.x), "=r"(v.y), "=r"(v.z), "=r"(v.w) : "r"(a) : "memory"); return v; }
__device__ __forceinline__ uint2 lds64(uint32_t a) { uint2 v; asm volatile("ld.shared.v2.u32 {%0,%1}, [%2];" : "=r"(v.x), "=r"(v.y) : "r"(a) : "memory"); return v; }
__device__ __forceinline__ uint32_t lds32(uint32_t a) { uint32_t v; asm volatile("ld.shared.u32 %0, [%1];" : "=r"(v) : "r"(a) : "memory"); return v; }
__device__ __forceinline__ uint32_t lds8(uint32_t a) { uint32_t v; asm volatile("ld.shared.u8 %0, [%1];" : "=r"(v) : "r"(a) : "memory"); return v; }
__device__ __forceinline__ void sts32(uint32_t a, uint32_t v) { asm volatile("st.shared.u32 [%0], %1;" :: "r"(a), "r"(v) : "memory"); }
__device__ __forceinline__ void sts8(uint32_t a, uint32_t v) { asm volatile("st.shared.u8 [%0], %1;" :: "r"(a), "r"(v) : "memory"); }
__device__ __forceinline__ void sts128(uint32_t a, uint4 v) { asm volatile("st.shared.v4.u32 [%0], {%1,%2,%3,%4};" :: "r"(a), "r"(v.x), "r"(v.y), "r"(v.z), "r"(v.w) : "memory"); }
__device__ __forceinline__ uint32_t atoms_add(uint32_t a, uint32_t v) { uint32_t r; asm volatile("atom.shared.add.u32 %0, [%1], %2;" : "=r"(r) : "r"(a), "r"(v) : "memory"); return r; }
__device__ __forceinline__ void reds_add(uint32_t a, uint32_t v) { asm volatile("red.shared.add.u32 [%0], %1;" :: "r"(a), "r"(v) : "memory"); }
__device__ __forceinline__ uint32_t atoms_add_p(bool p, uint32_t a, uint32_t v) {
    uint32_t r = 0;
    asm volatile("{\n.reg .pred p;\nsetp.ne.u32 p, %3, 0;\n@p atom.shared.add.u32 %0, [%1], %2;\n}" : "+r"(r) : "r"(a), "r"(v), "r"((uint32_t)p) : "memory");
    return r;
}
__device__ __forceinline__ uint32_t lds32_p(bool p, uint32_t a) {
    uint32_t r = 0;
    asm volatile("{\n.reg .pred p;\nsetp.ne.u32 p, %2, 0;\n@p ld.shared.u32 %0, [%1];\n}" : "+r"(r) : "r"(a), "r"((uint32_t)p) : "memory");
    return r;
}
__device__ __forceinline__ void sts32_p(bool p, uint32_t a, uint32_t v) {
    asm volatile("{\n.reg .pred p;\nsetp.ne.u32 p, %2, 0;\n@p st.shared.u32 [%0], %1;\n}" :: "r"(a), "r"(v), "r"((uint32_t)p) : "memory");
}
__device__ __forceinline__ void sts8_p(bool p, uint32_t a, uint32_t v) {
    asm volatile("{\n.reg .pred p;\nsetp.ne.u32 p, %2, 0;\n@p st.shared.u8 [%0], %1;\n}" :: "r"(a), "r"(v), "r"((uint32_t)p) : "memory");
}
__device__ __forceinline__ void st_piece(uint4* p, uint4 v) {
    asm volatile("{\n.reg .b128 q;\n.reg .b64 lo, hi;\nmov.b64 lo, {%1,%2};\nmov.b64 hi, {%3,%4};\nmov.b128 q, {lo, hi};\nst.relaxed.gpu.global.b128 [%0], q;\n}"
                 :: "l"(p), "r"(v.x), "r"(v.y), "r"(v.z), "r"(v.w) : "memory");
}
__device__ __forceinline__ uint4 ld_piece(const uint4* p) {
    uint4 v;
    asm volatile("{\n.reg .b128 q;\n.reg .b64 lo, hi;\nld.relaxed.gpu.global.b128 q, [%4];\nmov.b128 {lo, hi}, q;\nmov.b64 {%0,%1}, lo;\nmov.b64 {%2,%3}, hi;\n}"
                 : "=r"(v.x), "=r"(v.y), "=r"(v.z), "=r"(v.w) : "l"(p) : "memory");
    return v;
}
__device__ __forceinline__ void mbar_init(uint32_t bar, uint32_t cnt) { asm volatile("mbarrier.init.shared::cta.b64 [%0], %1;" :: "r"(bar), "r"(cnt) : "memory"); }
__device__ __forceinline__ void mbar_expect(uint32_t bar, uint32_t bytes) { asm volatile("mbarrier.arrive.expect_tx.shared::cta.b64 _, [%0], %1;" :: "r"(bar), "r"(bytes) : "memory"); }
__device__ __forceinline__ void mbar_wait(uint32_t bar, uint32_t parity) {
    uint32_t ok; int it = 0;
    do {
        asm volatile("{\n.reg .pred p;\nmbarrier.try_wait.parity.shared::cta.b64 p, [%1], %2;\nselp.u32 %0, 1, 0, p;\n}" : "=r"(ok) : "r"(bar), "r"(parity) : "memory");
    } while (!ok && ++it < (1 << 22));
}
__device__ __forceinline__ void tma_load2d(uint32_t dst, const CUtensorMap* tm, int c0, int c1, uint32_t bar) {
    asm volatile("cp.async.bulk.tensor.2d.shared::cluster.global.mbarrier::complete_tx::bytes [%0], [%1, {%3, %4}], [%2];"
                 :: "r"(dst), "l"(tm), "r"(bar), "r"(c0), "r"(c1) : "memory");
}
__device__ __forceinline__ void tma_load2d_mc(uint32_t dst, const CUtensorMap* tm, int c0, int c1, uint32_t bar) {
    asm volatile("cp.async.bulk.tensor.2d.shared::cluster.global.mbarrier::complete_tx::bytes.multicast::cluster [%0], [%1, {%3, %4}], [%2], %5;"
                 :: "r"(dst), "l"(tm), "r"(bar), "r"(c0), "r"(c1), "h"((uint16_t)3) : "memory");
}
__device__ __forceinline__ void tma_store2d(const CUtensorMap* tm, int c0, int c1, uint32_t src) {
    asm volatile("cp.async.bulk.tensor.2d.global.shared::cta.bulk_group [%0, {%2, %3}], [%1];"
                 :: "l"(tm), "r"(src), "r"(c0), "r"(c1) : "memory");
}
__device__ __forceinline__ void spin(uint32_t cycles) {
    uint32_t c0, c1;
    asm volatile("mov.u32 %0, %%clock;" : "=r"(c0));
    do { asm volatile("mov.u32 %0, %%clock;" : "=r"(c1)); } while (c1 - c0 < cycles);
}
__device__ __forceinline__ void lt_bar() { asm volatile("bar.sync 3, 256;" ::: "memory"); }
__device__ __forceinline__ void wg_bar(int id) { asm volatile("bar.sync %0, 128;" :: "r"(id) : "memory"); }

__device__ __forceinline__ void wgmma_n80(float (&d)[40], uint64_t da, uint64_t db, int acc) {
    asm volatile("{\n.reg .pred p;\nsetp.ne.b32 p, %42, 0;\n"
        "wgmma.mma_async.sync.aligned.m64n80k16.f32.bf16.bf16 "
        "{%0,%1,%2,%3,%4,%5,%6,%7,%8,%9,%10,%11,%12,%13,%14,%15,%16,%17,%18,%19,"
        "%20,%21,%22,%23,%24,%25,%26,%27,%28,%29,%30,%31,%32,%33,%34,%35,%36,%37,%38,%39}, "
        "%40, %41, p, 1, 1, 1, 0;\n}\n"
        : "+f"(d[0]), "+f"(d[1]), "+f"(d[2]), "+f"(d[3]), "+f"(d[4]), "+f"(d[5]), "+f"(d[6]), "+f"(d[7]), "+f"(d[8]), "+f"(d[9]),
          "+f"(d[10]), "+f"(d[11]), "+f"(d[12]), "+f"(d[13]), "+f"(d[14]), "+f"(d[15]), "+f"(d[16]), "+f"(d[17]), "+f"(d[18]), "+f"(d[19]),
          "+f"(d[20]), "+f"(d[21]), "+f"(d[22]), "+f"(d[23]), "+f"(d[24]), "+f"(d[25]), "+f"(d[26]), "+f"(d[27]), "+f"(d[28]), "+f"(d[29]),
          "+f"(d[30]), "+f"(d[31]), "+f"(d[32]), "+f"(d[33]), "+f"(d[34]), "+f"(d[35]), "+f"(d[36]), "+f"(d[37]), "+f"(d[38]), "+f"(d[39])
        : "l"(da), "l"(db), "r"(acc));
}

__device__ __forceinline__ void gemm_issue(float (&d)[40], uint32_t wbase, uint32_t xbase) {
    asm volatile("wgmma.fence.sync.aligned;" ::: "memory");
#pragma unroll
    for (int s = 0; s < 8; s++) {
        const uint32_t aa = wbase + s * 2048, ab = xbase + (s >> 2) * 10240 + (s & 3) * 32;
        const uint64_t da = (uint64_t)((aa & 0x3FFFF) >> 4) | ((uint64_t)64 << 16) | ((uint64_t)64 << 32) | ((uint64_t)1 << 62);
        const uint64_t db = (uint64_t)((ab & 0x3FFFF) >> 4) | ((uint64_t)1 << 16) | ((uint64_t)64 << 32) | ((uint64_t)1 << 62);
        wgmma_n80(d, da, db, s > 0);
    }
    asm volatile("wgmma.commit_group.sync.aligned;" ::: "memory");
}
__device__ __forceinline__ void gemm_wait(float (&d)[40]) {
    asm volatile("wgmma.wait_group.sync.aligned 0;" ::: "memory");
#pragma unroll
    for (int i = 0; i < 40; i++) asm volatile("" : "+f"(d[i]) :: "memory");
}
__device__ __forceinline__ void gemm_store(const float (&d)[40], float sc, uint32_t base, int w4, int lane) {
    const int mi = lane >> 3, rr = lane & 7;
    const uint32_t sa = base + (rr + 8 * (mi >> 1)) * 128 + (((2 * w4 + (mi & 1)) ^ rr) << 4);
#pragma unroll
    for (int p = 0; p < 5; p++) {
        const float* q = d + 8 * p;
        stsm4t(sa + p * 2048, pack_bf16(q[0] * sc, q[1] * sc), pack_bf16(q[2] * sc, q[3] * sc),
               pack_bf16(q[4] * sc, q[5] * sc), pack_bf16(q[6] * sc, q[7] * sc));
    }
}

struct Params {
    const int* dst;
    const int* src;
    unsigned* bar;
    uint4* xch;
    const bf16* gw;
    const bf16* e_attr;
    const char* table;
    bf16* out;
};

__global__ void __launch_bounds__(NTHR, 1)
egc_kernel(const Params p, const __grid_constant__ CUtensorMap tm_x, const __grid_constant__ CUtensorMap tm_g,
           const __grid_constant__ CUtensorMap tm_u, const __grid_constant__ CUtensorMap tm_v, const __grid_constant__ CUtensorMap tm_t) {
    extern __shared__ unsigned char smem_raw[];
    const uint32_t sb = ((uint32_t)__cvta_generic_to_shared(smem_raw) + 1023u) & ~1023u;
    const int tid = threadIdx.x, lane = tid & 31, b = blockIdx.x;
    const int w = __shfl_sync(0xffffffffu, tid >> 5, 0);
    const int wq = w >> 2, w4 = w & 3;
    const int g = lane >> 2, t = lane & 3, mi = lane >> 3, rr = lane & 7;
    TRACE(0);

    uint32_t Cf[8][4];
    auto load_cf = [&]() {
        const int krow = rr + 8 * (mi >> 1);
#pragma unroll
        for (int j = 0; j < 8; j++) {
            const int c = 2 * j + (mi & 1);
            ldsm4t(Cf[j], sb + SM_C + krow * 256 + ((c & 8) << 4) + (((c & 7) ^ rr) << 4));
#pragma unroll
            for (int q = 0; q < 4; q++) Cf[j][q] = mul_bf16x2(Cf[j][q], 0x3F003F00u);
        }
    };
    uint32_t xAf[8][2];
    float agg[8][4];
    const uint32_t ident = (g == 2 * t) ? 0x3F80u : ((g == 2 * t + 1) ? 0x3F800000u : 0u);
    const int nslot = (w < 12) ? 5 : 4;
    auto load_node_frags = [&]() {
        const int mynode = lds8(sb + SM_TNODE + w * 8 + ((rr < nslot) ? rr : 0));
#pragma unroll
        for (int jp = 0; jp < 4; jp++) {
            const int c = 4 * jp + mi;
            const uint32_t off = mynode * 128 + (((c & 7) ^ (mynode & 7)) << 4);
            uint32_t q[4];
            ldsm4t(q, sb + SM_WA + (c >> 3) * 16384 + off);
            xAf[2 * jp][0] = q[0]; xAf[2 * jp][1] = q[1]; xAf[2 * jp + 1][0] = q[2]; xAf[2 * jp + 1][1] = q[3];
            ldsm4t(q, sb + SM_X + (c >> 3) * 10240 + off);
            mma1688_z(agg[2 * jp], q[0], q[1], ident);
            mma1688_z(agg[2 * jp + 1], q[2], q[3], ident);
        }
    };
    uint32_t bar_target = 0;
    constexpr int LT = 256;
    if (wq < 2) {
        uint32_t epoch = 0;
        {
            const int r = tid >> 4, c = tid & 15;
            cp16(sb + SM_C + r * 256 + ((c & 8) << 4) + (((c & 7) ^ (r & 7)) << 4), p.gw + (256 + r) * 128 + c * 8);
            cp_commit();
        }
        if (tid == 0) {
            asm volatile("ld.relaxed.gpu.global.u32 %0, [%1];" : "=r"(epoch) : "l"(p.bar) : "memory");
            for (int i = 0; i < 9; i++) mbar_init(sb + SM_BAR + i * 8, 1);
            asm volatile("fence.mbarrier_init.release.cluster;" ::: "memory");
            const uint32_t bx = sb + SM_BAR;
            mbar_expect(bx, 20480);
#pragma unroll
            for (int i = 0; i < 8; i++) mbar_expect(bx + 8 + i * 8, 16384);
            spin(START_DELAY);
            tma_load2d(sb + SM_X, &tm_x, 0, b * NPC, bx);
            tma_load2d(sb + SM_X + 10240, &tm_x, 64, b * NPC, bx);
            tma_load2d(sb + SM_R0, &tm_g, 0, 128, bx + 8);
            tma_load2d(sb + SM_R0 + 16384, &tm_g, 64, 128, bx + 16);
            tma_load2d(sb + SM_R0 + 2 * 16384, &tm_v, 0, 0, bx + 24);
            tma_load2d(sb + SM_R0 + 3 * 16384, &tm_v, 64, 0, bx + 32);
        }
        cp_wait<0>();
        asm volatile("bar.sync 6, 256;" ::: "memory");
        asm volatile("bar.arrive 8, 512;" ::: "memory");
        TRACE(1);
        load_cf();
        float d[40];
        const uint32_t xt = sb + SM_X;
        const bool elect = (w4 == 0 && lane == 0);
        mbar_wait(sb + SM_BAR, 0);
#pragma unroll 1
        for (int r = 0; r < 4; r++) {
            const uint32_t wt = sb + ((r < 2) ? SM_R0 + r * 32768 : ((r == 2) ? SM_WA : SM_WU)) + wq * 16384;
            mbar_wait(sb + SM_BAR + 8 + (2 * r + wq) * 8, 0);
            TRACE(2 + 2 * r);
            gemm_issue(d, wt, xt);
            if (r == 0 && tid == 0) {
#pragma unroll
                for (int i = 0; i < 2; i++) {
                    tma_load2d(sb + SM_WA + i * 16384, &tm_g, i * 64, 0, sb + SM_BAR + 8 + (4 + i) * 8);
                    tma_load2d(sb + SM_WU + i * 16384, &tm_u, i * 64, 0, sb + SM_BAR + 8 + (6 + i) * 8);
                }
            }
            if (r == 2) {
                asm volatile("bar.sync 4, 512;" ::: "memory");
                if (elect) {
                    asm volatile("cp.async.bulk.wait_group 0;" ::: "memory");
                    asm volatile("fence.proxy.async.global;" ::: "memory");
                    asm volatile("red.relaxed.gpu.global.add.u32 [%0], 1;" :: "l"(p.bar) : "memory");
                }
            }
            if (r == 3 && tid == 0) {
                const int e0 = b * ECH, ne = min(ECH, EE - e0);
                asm volatile("cp.async.bulk.prefetch.L2.global [%0], %1;" :: "l"(p.e_attr + (size_t)e0 * 16), "r"(ne * 32) : "memory");
            }
            __syncwarp();
            gemm_wait(d);
            if (r < 3) wg_bar(1 + wq); else asm volatile("bar.sync 6, 256;" ::: "memory");
            gemm_store(d, (r == 1) ? 0.25f : 0.5f, (r < 3) ? wt : xt + wq * 10240, w4, lane);
            if (r < 2) {
                asm volatile("fence.proxy.async.shared::cta;" ::: "memory");
                wg_bar(1 + wq);
                if (elect) {
                    tma_store2d(&tm_t, (2 * r + wq) * 64, b * NPC, wt);
                    asm volatile("cp.async.bulk.commit_group;" ::: "memory");
                }
                __syncwarp();
            }
            TRACE(3 + 2 * r);
        }

        bar_target = (epoch / (2 * NCTA) + 1) * (2 * NCTA);
        TRACE(9);
    } else {
        const int lt = tid - LT;
        int ed[5], es[5];
        uint32_t epoch = 0;
#pragma unroll
        for (int m = 0; m < 5; m++) {
            const int k = lt + m * LT, e = b * ECH + k;
            ed[m] = ((k < ECH) && (e < EE)) ? __ldg(p.dst + e) : -1;
        }
#pragma unroll
        for (int m = 0; m < 5; m++) {
            const int k = lt + m * LT, e = b * ECH + k;
            es[m] = ((k < ECH) && (e < EE)) ? __ldg(p.src + e) : 0;
        }
        if (lt == 0) asm volatile("ld.relaxed.gpu.global.u32 %0, [%1];" : "=r"(epoch) : "l"(p.bar) : "memory");
        if (lt < 136) sts32(sb + SM_HIST + lt * 4, 0);
        if (lt < 128) { sts32(sb + SM_KEYS + lt * 4, 0); sts32(sb + SM_TDEG + lt * 4, 0); }
        if (lt < 64) sts32(sb + SM_DBIN + lt * 4, 0);
        if (lt == 0) sts32(sb + SM_FLAG, 0);
        lt_bar();
        TRACE(24);
        {
            uint32_t jj[5], rk[5];
#pragma unroll
            for (int m = 0; m < 5; m++) {
                jj[m] = (ed[m] >= 0) ? (((uint32_t)ed[m] * 55189u) >> 22) : (132 + (lane & 3));
                rk[m] = atoms_add(sb + SM_HIST + jj[m] * 4, 1);
            }
#pragma unroll
            for (int m = 0; m < 5; m++) {
                const uint32_t loc = (uint32_t)ed[m] - jj[m] * NPC;
                const uint32_t q = (rk[m] * 43691u) >> 17;
                const uint32_t off = jj[m] * (PIECES * 16) + q * 16 + (rk[m] - 3 * q + 1) * 4;
                sts32(sb + SM_S + ((ed[m] >= 0 && rk[m] < XCAP) ? off : NCTA * PIECES * 16 + lane * 4),
                      (uint32_t)es[m] | (loc << 14) | ((uint32_t)(lt + m * LT) << 21));
            }
        }
        if (lt == 0) sts32(sb + SM_FLAG + 4, epoch / (2 * NCTA));
        TRACE(25);
        lt_bar();
        const uint32_t bar_q = lds32(sb + SM_FLAG + 4);
        epoch = (bar_q + 1) & 0xFFFFFF;
        {
            uint4 v[6]; uint32_t c[6];
#pragma unroll
            for (int m = 0; m < 6; m++) {
                const int pc = min(lt + m * LT, NCTA * PIECES - 1);
                v[m] = lds128(sb + SM_S + pc * 16);
                c[m] = lds32(sb + SM_HIST + ((pc * 6554) >> 16) * 4);
            }
#pragma unroll
            for (int m = 0; m < 6; m++) {
                const int pc = lt + m * LT;
                const int j = (pc * 6554) >> 16, q = pc - j * PIECES;
                if ((m < 5 || pc < NCTA * PIECES) && (q < 4 || c[m] > 3 * (q & ~1) || b >= 128)) {
                    v[m].x = (epoch << 8) | min(c[m], 255u);
                    st_piece(p.xch + (((j * (PIECES / 2) + (q >> 1)) * NCTA + b) * 2 + (q & 1)), v[m]);
                }
            }
        }
        TRACE(46);
        asm volatile("bar.arrive 4, 512;" ::: "memory");
        lt_bar();
        if (lt == 0) asm volatile("red.relaxed.gpu.global.add.u32 [%0], 1;" :: "l"(p.bar + 1) : "memory");
        asm volatile("bar.sync 8, 512;" ::: "memory");
        load_cf();
        if (lt == 0) {
            uint32_t v; int it = 0;
            const uint32_t target = bar_q * NCTA + NCTA * 17 / 20;
            do { asm volatile("ld.relaxed.gpu.global.u32 %0, [%1];" : "=r"(v) : "l"(p.bar + 1) : "memory"); }
            while ((int)(v - target) < 0 && ++it < SPIN_LIMIT);
        }
        lt_bar();
        TRACE(26);
        uint4 pv[6];
        const int pi5 = 128 + ((lt >> 1) & 3), pq5 = 2 * (lt >> 3) + (lt & 1);
        const uint4* px0 = p.xch + b * (NCTA * PIECES) + lt;
        const uint4* px5 = p.xch + b * (NCTA * PIECES) + (lt >> 3) * (2 * NCTA) + 256 + (lt & 7);
        const uint32_t tg = epoch << 8;
        auto fetch = [&](const uint4* a) {
            uint4 v = ld_piece(a);
            int it = 0;
            while (((v.x ^ tg) >> 8) && ++it < SPIN_LIMIT) { __nanosleep(100); v = ld_piece(a); }
            return v;
        };
        pv[0] = ld_piece(px0);
        pv[1] = ld_piece(px0 + 2 * NCTA);
        pv[5] = (lt < 4 * PIECES) ? ld_piece(px5) : make_uint4(tg, 0, 0, 0);
        for (int it = 0; (((pv[0].x ^ tg) | (pv[1].x ^ tg) | (pv[5].x ^ tg)) >> 8) && it < SPIN_LIMIT; it++) {
            __nanosleep(100);
            if ((pv[0].x ^ tg) >> 8) pv[0] = ld_piece(px0);
            if ((pv[1].x ^ tg) >> 8) pv[1] = ld_piece(px0 + 2 * NCTA);
            if ((pv[5].x ^ tg) >> 8) pv[5] = ld_piece(px5);
        }
        const int cnt = pv[0].x & 255, cnt5 = pv[5].x & 255;
#pragma unroll
        for (int m = 2; m < 5; m++) pv[m] = (cnt > 6 * m) ? ld_piece(px0 + m * (2 * NCTA)) : make_uint4(tg, 0, 0, 0);
        if (cnt > XCAP || cnt5 > XCAP) sts32(sb + SM_FLAG, 1);
        TRACE(27);
        const uint32_t dmy = (96 + lane) * 4;
        uint32_t ao[9], rk[9];
        auto count = [&](int m, int o) {
            const int nv = (m < 5) ? cnt - 3 * (2 * m + (lt & 1)) : cnt5 - 3 * pq5;
#pragma unroll
            for (int s = 0; s < 3; s++) {
                const uint32_t pl = (s == 0) ? pv[m].y : ((s == 1) ? pv[m].z : pv[m].w);
                ao[o + s] = (nv > s) ? ((pl >> 12) & 0x1FC) : dmy;
                rk[o + s] = atoms_add(sb + SM_KEYS + ao[o + s], 1);
            }
        };
        auto put = [&](int m, int o) {
            const uint32_t e0s = (uint32_t)(((m < 5) ? (lt >> 1) : pi5) * ECH) << 14;
#pragma unroll
            for (int s = 0; s < 3; s++) {
                const uint32_t pl = (s == 0) ? pv[m].y : ((s == 1) ? pv[m].z : pv[m].w);
                const bool ok = ao[o + s] < 96 * 4 && rk[o + s] < NCAP;
                sts32(sb + SM_NL + (ok ? ao[o + s] * NCAP + rk[o + s] * 4 : NPC * NCAP * 4 + lane * 4), (pl & 0x3FFF) + ((pl >> 21) << 14) + e0s);
            }
        };
        count(0, 0);
        count(1, 3);
        const bool has5 = lt < 64;
        if (has5) count(5, 6);
        put(0, 0);
        put(1, 3);
        if (has5) put(5, 6);
        if (((pv[2].x ^ tg) | (pv[3].x ^ tg) | (pv[4].x ^ tg)) >> 8) {
#pragma unroll
            for (int m = 2; m < 5; m++) if (cnt > 6 * m) pv[m] = fetch(px0 + m * (2 * NCTA));
        }
#pragma unroll
        for (int m = 2; m < 5; m++) {
            if (__any_sync(0xffffffffu, cnt > 6 * m)) { count(m, 0); put(m, 0); }
        }
        TRACE(28);
        lt_bar();
        if (lt < 96) {
            const uint32_t deg = (lt < NPC) ? lds32(sb + SM_KEYS + lt * 4) : 0;
            const uint32_t bin = 63 - min(deg, 63u);
            const uint32_t r0 = atoms_add_p(lt < NPC, sb + SM_DBIN + bin * 4, 1);
            if (deg > NCAP) sts32(sb + SM_FLAG, 1);
            asm volatile("bar.sync 5, 96;" ::: "memory");
            const uint2 c2 = lds64(sb + SM_DBIN + lane * 8);
            uint32_t inc = c2.x + c2.y;
#pragma unroll
            for (int o = 1; o < 32; o <<= 1) { const uint32_t u = __shfl_up_sync(0xffffffffu, inc, o); if (lane >= o) inc += u; }
            const uint32_t ex = inc - c2.x - c2.y;
            const uint32_t pe = __shfl_sync(0xffffffffu, ex, bin >> 1), p0 = __shfl_sync(0xffffffffu, c2.x, bin >> 1);
            const int rank = pe + ((bin & 1) ? p0 : 0) + r0;
            const int k = rank >> 4, pos = rank & 15;
            const int tile = (k == 4) ? 11 - pos : ((pos < 4) ? 12 + ((k & 1) ? 3 - pos : pos) : ((k < 3) ? pos - 4 : 15 - pos));
            if (lt < NPC) {
                sts32(sb + SM_TDEG + (tile * 8 + k) * 4, deg);
                sts8(sb + SM_TNODE + tile * 8 + k, lt);
            }
        }
        TRACE(29);
        TRACE(30);
    }
    TRACE(31);
    __syncthreads();
    TRACE(32);
    bool slow = lds32(sb + SM_FLAG) != 0;

    constexpr uint32_t RD = SM_R1 - SM_R0;
    const uint32_t ring0 = sb + SM_R0 + w * STAGE;
    const char* tab_l = p.table + lane * 16;
    asm volatile("" : "+l"(tab_l));
    const char* e_l = (const char*)p.e_attr + (mi & 1) * 16;
    asm volatile("" : "+l"(e_l));
    const uint32_t cpo = lane * 16;
    const uint32_t elo = 4096 + rr * 32 + (((mi & 1) ^ ((rr >> 2) & 1)) << 4);
    const uint32_t lsrc = sb + SM_LSE + w * TCAP * 4, lid = sb + SM_LID + w * TCAP;
    const uint32_t lec = rr * 4;

    auto issue_full = [&](uint32_t lp, uint32_t dl) {
        const uint4 s0 = lds128(lp), s1 = lds128(lp + 16);
        const uint32_t eo = lds32(lp + lec);
        const uint32_t sv[8] = {s0.x, s0.y, s0.z, s0.w, s1.x, s1.y, s1.z, s1.w};
#pragma unroll
        for (int j = 0; j < 8; j++) cp16(ring0 + dl + (cpo ^ (j << 4)) + j * 512, madw(sv[j] & 0x3FFF, 512, tab_l));
        cp16(ring0 + dl + elo, madw(eo >> 14, 32, e_l));
    };
    auto issue0 = [&]() {
        const int cnt = lds32(sb + SM_TCNT + w * 4), nit = (cnt + 7) >> 3;
        if (nit > 0) {
            const int pad = nit * 8 - cnt;
            const uint4 s0 = lds128(lsrc), s1 = lds128(lsrc + 16);
            const uint32_t eo = lds32(lsrc + lec);
            const uint32_t sv[8] = {s0.x, s0.y, s0.z, s0.w, s1.x, s1.y, s1.z, s1.w};
#pragma unroll
            for (int j = 0; j < 8; j++) cp16z(ring0 + (cpo ^ (j << 4)) + j * 512, madw(sv[j] & 0x3FFF, 512, tab_l), (j >= pad) ? 16 : 0);
            cp16z(ring0 + elo, madw(eo >> 14, 32, e_l), (rr >= pad) ? 16 : 0);
        }
        cp_commit();
    };
    auto issue1 = [&]() {
        if ((int)lds32(sb + SM_TCNT + w * 4) > 8) issue_full(lsrc + 32, RD);
        cp_commit();
    };
    uint32_t bar_v = 0;
    bool over = false;
    if (tid == 0) asm volatile("ld.relaxed.gpu.global.u32 %0, [%1];" : "=r"(bar_v) : "l"(p.bar) : "memory");
    if (!slow) {
        const uint2 tn = lds64(sb + SM_TNODE + w * 8);
        const uint4 dg = lds128(sb + SM_TDEG + w * 32);
        const uint32_t p1 = dg.x, p2 = p1 + dg.y, p3 = p2 + dg.z, p4 = p3 + dg.w, tot = p4 + lds32(sb + SM_TDEG + w * 32 + 16);
        const uint32_t pad = (0u - tot) & 7u;
        if (lane == 0) sts32(sb + SM_TCNT + w * 4, tot);
        over = tot + pad > TCAP;
        uint32_t wd[TCAP / 32], sl[TCAP / 32];
#pragma unroll
        for (int r = 0; r < TCAP / 32; r++) {
            const uint32_t q = lane + 32 * r - pad;
            sl[r] = (q >= p1) + (q >= p2) + (q >= p3) + (q >= p4);
            const uint32_t pre = (q >= p4) ? p4 : ((q >= p3) ? p3 : ((q >= p2) ? p2 : ((q >= p1) ? p1 : 0)));
            const uint32_t node = prmt(tn.x, tn.y, sl[r]) & 0xFF;
            wd[r] = lds32(sb + SM_NL + ((q < tot) ? (node * NCAP + q - pre) * 4 : 0));
        }
#pragma unroll
        for (int r = 0; r < TCAP / 32; r++) {
            const uint32_t q = lane + 32 * r - pad;
            sts32(lsrc + (lane + 32 * r) * 4, (q < tot) ? wd[r] : 0);
            sts8(lid + lane + 32 * r, (q < tot) ? sl[r] * 16 : 0x7F);
        }
    }
    TRACE(10);
    if (tid == 0) {
        int it = 0;
        while ((int)(bar_v - bar_target) < 0 && ++it < SPIN_LIMIT)
            asm volatile("ld.relaxed.gpu.global.u32 %0, [%1];" : "=r"(bar_v) : "l"(p.bar) : "memory");
    }
    slow = __syncthreads_or(slow || over);
    TRACE(11);
    if (!slow) {
        issue0();
        issue1();
    } else {
        if (tid < NPC) sts8(sb + SM_TNODE + (tid & 15) * 8 + (tid >> 4), tid);
        __syncthreads();
    }
    TRACE(33);
    load_node_frags();
    TRACE(34);

    const uint32_t ldo = rr * 512 + ((mi ^ rr) << 4);
    const uint32_t sel = (g | ((8 | g) << 4) | (g << 8) | ((8 | g) << 12)) |
                         (((2 * t) | ((8 | (2 * t)) << 4) | ((2 * t + 1) << 8) | ((8 | (2 * t + 1)) << 12)) << 16);
    const uint32_t gg = (g * 16) | ((g * 16) << 16);
    const uint32_t tt = (t * 32) | ((t * 32 + 16) << 16);

    auto compute = [&](uint32_t st, uint32_t idp) {
        uint32_t eb[2];
        ldsm2(eb, st + elo);
        const uint2 iw = lds64(idp);
        const uint32_t sx = seteq_bf16x2(prmt(iw.x, iw.y, sel), tt);
        const uint32_t sa = seteq_bf16x2(prmt(iw.x, iw.y, sel >> 16), gg);
#pragma unroll
        for (int jj = 0; jj < 4; jj++) {
            uint32_t xb[4], hv[4];
            const uint32_t la = st + (ldo ^ ((jj & 1) << 6)) + (jj >> 1) * 128;
            ldsm4(xb, la);
            ldsm4t(hv, la + 256);
#pragma unroll
            for (int u = 0; u < 2; u++) {
                const int j = 2 * jj + u;
                float d[4];
                mma16816_z(d, Cf[j][0], Cf[j][1], Cf[j][2], Cf[j][3], eb[0], eb[1]);
                mma1688(d, xAf[j][0], xAf[j][1], sx);
                mma16816(d, ident, 0u, 0u, ident, xb[2 * u], xb[2 * u + 1]);
                const uint32_t m0 = fma_bf16x2(pack_bf16(tanh_ap(d[0]), tanh_ap(d[1])), hv[2 * u], hv[2 * u]);
                const uint32_t m1 = fma_bf16x2(pack_bf16(tanh_ap(d[2]), tanh_ap(d[3])), hv[2 * u + 1], hv[2 * u + 1]);
                mma1688(agg[j], m0, m1, sa);
            }
        }
    };

    const int nseg = slow ? NSEG : 1;
#pragma unroll 1
    for (int seg = 0; seg < nseg; seg++) {
        if (slow) {
            __syncthreads();
            if (tid < 16) sts32(sb + SM_TCNT + tid * 4, 0);
            __syncthreads();
            const int e = seg * TCAP + tid;
            int loc = -1; uint32_t r = 0;
            if (tid < TCAP && e < EE) {
                const int dd = __ldg(p.dst + e) - b * NPC;
                if (dd >= 0 && dd < NPC) { loc = dd; r = atoms_add(sb + SM_TCNT + (loc & 15) * 4, 1); }
            }
            __syncthreads();
            if (loc >= 0) {
                const uint32_t tile = loc & 15, tot = lds32(sb + SM_TCNT + tile * 4);
                const uint32_t pos = tile * TCAP + ((0u - tot) & 7u) + r;
                sts32(sb + SM_LSE + pos * 4, (uint32_t)__ldg(p.src + e) | ((uint32_t)e << 14));
                sts8(sb + SM_LID + pos, (loc >> 4) << 4);
            }
            const int pad = (0 - (int)lds32(sb + SM_TCNT + w * 4)) & 7;
            if (lane < pad) { sts8(sb + SM_LID + w * TCAP + lane, 0x7F); sts32(sb + SM_LSE + (w * TCAP + lane) * 4, 0); }
            __syncthreads();
            issue0();
            issue1();
        }
        const int nit = __shfl_sync(0xffffffffu, ((int)lds32(sb + SM_TCNT + w * 4) + 7) >> 3, 0);
        uint32_t st = ring0, so = ring0 + RD, lp = lsrc + 32, idp = lid;
        const uint32_t lend = lsrc + nit * 32;
        constexpr int AVG_NIT = (EE + NCTA * 128 - 1) / (NCTA * 128);
        constexpr int HEAVY = EE / NN * NPC * 207 / 200;
        const int ctot = __reduce_add_sync(0xffffffffu, (lane < 16) ? (int)lds32(sb + SM_TCNT + lane * 4) : 0);
        if (nit <= AVG_NIT && ctot <= HEAVY) {
#pragma unroll 1
            for (; lp <= lend; lp += 32, idp += 8) {
                if (idp == lid) cp_wait<1>(); else cp_wait<0>();
                __syncwarp();
                if (idp != lid && lp < lend) issue_full(lp, so - ring0);
                cp_commit();
                compute(st, idp);
                const uint32_t tmp = st; st = so; so = tmp;
            }
        } else {
#pragma unroll 1
            for (; lp <= lend; lp += 32, idp += 8) {
                cp_wait<1>();
                __syncwarp();
                compute(st, idp);
                __syncwarp();
                if (lp + 32 < lend) issue_full(lp + 32, st - ring0);
                cp_commit();
                const uint32_t tmp = st; st = so; so = tmp;
            }
        }
        cp_wait<0>();
        __syncwarp();
    }
    TRACE(35);

    {
        uint32_t o[8][2];
#pragma unroll
        for (int j = 0; j < 8; j++) {
            float v[4];
#pragma unroll
            for (int q = 0; q < 4; q++) { const float h = agg[j][q]; v[q] = fmaf(h, tanh_ap(h), h); }
            o[j][0] = pack_bf16(v[0], v[1]); o[j][1] = pack_bf16(v[2], v[3]);
        }
#pragma unroll
        for (int jp = 0; jp < 4; jp++) {
            const int c = 4 * jp + mi;
            stsm4t(ring0 + rr * 256 + ((c & 8) << 4) + (((c & 7) ^ rr) << 4), o[2 * jp][0], o[2 * jp][1], o[2 * jp + 1][0], o[2 * jp + 1][1]);
        }
        __syncwarp();
#pragma unroll
        for (int i = 0; i < 3; i++) {
            const int idx = lane + 32 * i, row = idx >> 4, c = idx & 15;
            const int nd = b * NPC + (int)lds8(sb + SM_TNODE + w * 8 + (row & 7));
            if (row < nslot && nd < NN) {
                const uint4 v = lds128(ring0 + row * 256 + ((c & 8) << 4) + (((c & 7) ^ row) << 4));
                *(uint4*)((char*)p.out + (size_t)nd * 256 + c * 16) = v;
            }
        }
    }
    TRACE(36);
}

__device__ __align__(16) bf16 g_fb_xa[NN * 128];
__device__ __align__(16) float g_fb_h[NN * 128];

__global__ void fb_node_kernel(const bf16* x, const bf16* uw, const bf16* vw, const bf16* gw, bf16* table) {
    __shared__ float xs[128];
    const int n = blockIdx.x, f = threadIdx.x;
    xs[f] = __bfloat162float(x[n * 128 + f]);
    __syncthreads();
    float a = 0.f, bb = 0.f, v = 0.f, u = 0.f;
    for (int k = 0; k < 128; k++) {
        const float xv = xs[k];
        a += xv * __bfloat162float(gw[k * 128 + f]);
        bb += xv * __bfloat162float(gw[(128 + k) * 128 + f]);
        v += xv * __bfloat162float(vw[k * 128 + f]);
        u += xv * __bfloat162float(uw[k * 128 + f]);
    }
    table[n * 256 + f] = __float2bfloat16(0.5f * bb);
    table[n * 256 + 128 + f] = __float2bfloat16(0.25f * v);
    g_fb_xa[n * 128 + f] = __float2bfloat16(0.5f * a);
    g_fb_h[n * 128 + f] = 0.5f * u;
}
__global__ void fb_edge_kernel(const bf16* e_attr, const int* src, const int* dst, const bf16* gw, const bf16* table) {
    const int e = blockIdx.x, f = threadIdx.x, s = src[e], d = dst[e];
    float z = 0.f;
    for (int k = 0; k < 16; k++) z += __bfloat162float(e_attr[e * 16 + k]) * __bfloat162float(gw[(256 + k) * 128 + f]);
    z = 0.5f * z + __bfloat162float(g_fb_xa[d * 128 + f]) + __bfloat162float(table[s * 256 + f]);
    const float hv = __bfloat162float(table[s * 256 + 128 + f]);
    atomicAdd(&g_fb_h[d * 128 + f], fmaf(hv, tanhf(z), hv));
}
__global__ void fb_out_kernel(bf16* out) {
    const int i = blockIdx.x * 128 + threadIdx.x;
    const float h = g_fb_h[i];
    out[i] = __float2bfloat16(fmaf(h, tanhf(h), h));
}

typedef CUresult (*EncodeFn)(CUtensorMap*, CUtensorMapDataType, cuuint32_t, void*, const cuuint64_t*, const cuuint64_t*,
                             const cuuint32_t*, const cuuint32_t*, CUtensorMapInterleave, CUtensorMapSwizzle,
                             CUtensorMapL2promotion, CUtensorMapFloatOOBfill);

static void make_map(EncodeFn enc, CUtensorMap* tm, const void* base, int rows, int cols, int box_rows) {
    cuuint64_t dims[2] = {(cuuint64_t)cols, (cuuint64_t)rows};
    cuuint64_t strides[1] = {(cuuint64_t)cols * 2};
    cuuint32_t box[2] = {64, (cuuint32_t)box_rows};
    cuuint32_t es[2] = {1, 1};
    enc(tm, CU_TENSOR_MAP_DATA_TYPE_BFLOAT16, 2, (void*)base, dims, strides, box, es, CU_TENSOR_MAP_INTERLEAVE_NONE,
        CU_TENSOR_MAP_SWIZZLE_128B, CU_TENSOR_MAP_L2_PROMOTION_NONE, CU_TENSOR_MAP_FLOAT_OOB_FILL_NONE);
}

}

extern "C" void kernel_launch(void* const* d_in, const int* in_sizes, int n_in, void* d_out, int out_size) {
    using namespace egc;
    (void)in_sizes; (void)n_in; (void)out_size;
    static EncodeFn enc = nullptr;
    static void* table = nullptr;
    static void* xch = nullptr;
    static void* bar = nullptr;
    static bool persistent = false;
    if (!enc) {
        void* fn = nullptr;
        cudaDriverEntryPointQueryResult qr;
        cudaGetDriverEntryPoint("cuTensorMapEncodeTiled", &fn, cudaEnableDefault, &qr);
        enc = (EncodeFn)fn;
        cudaGetSymbolAddress(&table, g_table);
        cudaGetSymbolAddress(&xch, g_xch);
        cudaGetSymbolAddress(&bar, g_bar);
        cudaFuncSetAttribute(egc_kernel, cudaFuncAttributeMaxDynamicSharedMemorySize, SMEM_BYTES);
        int dev = 0, sms = 0, per_sm = 0;
        cudaGetDevice(&dev);
        cudaDeviceGetAttribute(&sms, cudaDevAttrMultiProcessorCount, dev);
        cudaOccupancyMaxActiveBlocksPerMultiprocessor(&per_sm, egc_kernel, NTHR, SMEM_BYTES);
        persistent = enc != nullptr && sms * per_sm >= NCTA;
    }
    if (!persistent) {
        const bf16* x = (const bf16*)d_in[0];
        fb_node_kernel<<<NN, 128, 0, cudaStreamPerThread>>>(x, (const bf16*)d_in[4], (const bf16*)d_in[5], (const bf16*)d_in[6], (bf16*)table);
        fb_edge_kernel<<<EE, 128, 0, cudaStreamPerThread>>>((const bf16*)d_in[1], (const int*)d_in[2], (const int*)d_in[3], (const bf16*)d_in[6], (const bf16*)table);
        fb_out_kernel<<<NN, 128, 0, cudaStreamPerThread>>>((bf16*)d_out);
        return;
    }
    CUtensorMap tm_x, tm_g, tm_u, tm_v, tm_t;
    make_map(enc, &tm_x, d_in[0], NN, 128, 80);
    make_map(enc, &tm_u, d_in[4], 128, 128, 128);
    make_map(enc, &tm_v, d_in[5], 128, 128, 128);
    make_map(enc, &tm_g, d_in[6], 272, 128, 128);
    make_map(enc, &tm_t, table, NN, 256, NPC);
    Params p;
    p.e_attr = (const bf16*)d_in[1];
    p.src = (const int*)d_in[2];
    p.dst = (const int*)d_in[3];
    p.gw = (const bf16*)d_in[6];
    p.out = (bf16*)d_out;
    p.bar = (unsigned*)bar;
    p.xch = (uint4*)xch;
    p.table = (const char*)table;
    egc_kernel<<<NCTA, NTHR, SMEM_BYTES, cudaStreamPerThread>>>(p, tm_x, tm_g, tm_u, tm_v, tm_t);
}
```

```cpp
#include <cuda_runtime.h>
#include <cuda_bf16.h>
#include <cuda.h>
#include <stdint.h>
#include <type_traits>

namespace egc {

typedef __nv_bfloat16 bf16;

constexpr int NN = 10000, EE = 160000;
constexpr int NCTA = 132, NPC = 76, ECH = 1216, NTHR = 512;
constexpr int PIECES = 10, XCAP = 3 * PIECES;
constexpr int TCAP = 96;
constexpr int NSEG = (EE + TCAP - 1) / TCAP;
constexpr int SPIN_LIMIT = 1 << 20;
constexpr uint32_t START_DELAY = 420;

constexpr int STAGE = 4352;
constexpr int SM_R0 = 0;
constexpr int SM_R1 = 16 * STAGE;
constexpr int SM_S = SM_R1;
constexpr int SM_WU = SM_R1 + 8 * STAGE;
constexpr int SM_WA = SM_R1 + 16 * STAGE;
constexpr int SM_X = SM_WA + 32768;
constexpr int SM_C = SM_X + 20480;
constexpr int SM_LSE = SM_C + 4096;
constexpr int SM_LID = SM_LSE + 6144 + 128;
constexpr int SM_HIST = SM_LID + 1536 + 32;
constexpr int SM_KEYS = SM_HIST + 544;
constexpr int SM_CURS = SM_KEYS + 512;
constexpr int SM_DBIN = SM_CURS + 512;
constexpr int SM_TDEG = SM_DBIN + 256;
constexpr int SM_TNODE = SM_TDEG + 512;
constexpr int SM_TCNT = SM_TNODE + 128;
constexpr int SM_FLAG = SM_TCNT + 64;
constexpr int NCAP = 40;
constexpr int SM_NL = SM_FLAG + 16;
constexpr int SM_BAR = SM_NL + NPC * NCAP * 4 + 128;
constexpr int SM_TRACE = SM_BAR + 9 * 8 + 8;
constexpr int SM_END = SM_TRACE + 2 * 48 * 4;
constexpr int SMEM_BYTES = SM_END + 1024;

__device__ __align__(1024) uint4 g_table[NN * 32];
__device__ __align__(1024) uint4 g_xch[NCTA * NCTA * PIECES];
__device__ __align__(128) unsigned g_bar[32];
#define TRACE(i) do {} while (0)

__device__ __forceinline__ void mma16816(float* d, uint32_t a0, uint32_t a1, uint32_t a2, uint32_t a3, uint32_t b0, uint32_t b1) {
    asm("mma.sync.aligned.m16n8k16.row.col.f32.bf16.bf16.f32 {%0,%1,%2,%3}, {%4,%5,%6,%7}, {%8,%9}, {%0,%1,%2,%3};"
        : "+f"(d[0]), "+f"(d[1]), "+f"(d[2]), "+f"(d[3]) : "r"(a0), "r"(a1), "r"(a2), "r"(a3), "r"(b0), "r"(b1));
}
__device__ __forceinline__ void mma16816_z(float* d, uint32_t a0, uint32_t a1, uint32_t a2, uint32_t a3, uint32_t b0, uint32_t b1) {
    asm("mma.sync.aligned.m16n8k16.row.col.f32.bf16.bf16.f32 {%0,%1,%2,%3}, {%4,%5,%6,%7}, {%8,%9}, {%10,%10,%10,%10};"
        : "=f"(d[0]), "=f"(d[1]), "=f"(d[2]), "=f"(d[3]) : "r"(a0), "r"(a1), "r"(a2), "r"(a3), "r"(b0), "r"(b1), "f"(0.f));
}
__device__ __forceinline__ void mma1688(float* d, uint32_t a0, uint32_t a1, uint32_t b0) {
    asm("mma.sync.aligned.m16n8k8.row.col.f32.bf16.bf16.f32 {%0,%1,%2,%3}, {%4,%5}, {%6}, {%0,%1,%2,%3};"
        : "+f"(d[0]), "+f"(d[1]), "+f"(d[2]), "+f"(d[3]) : "r"(a0), "r"(a1), "r"(b0));
}
__device__ __forceinline__ void mma1688_z(float* d, uint32_t a0, uint32_t a1, uint32_t b0) {
    asm("mma.sync.aligned.m16n8k8.row.col.f32.bf16.bf16.f32 {%0,%1,%2,%3}, {%4,%5}, {%6}, {%7,%7,%7,%7};"
        : "=f"(d[0]), "=f"(d[1]), "=f"(d[2]), "=f"(d[3]) : "r"(a0), "r"(a1), "r"(b0), "f"(0.f));
}
__device__ __forceinline__ void ldsm4(uint32_t* r, uint32_t addr) {
    asm volatile("ldmatrix.sync.aligned.m8n8.x4.shared.b16 {%0,%1,%2,%3}, [%4];" : "=r"(r[0]), "=r"(r[1]), "=r"(r[2]), "=r"(r[3]) : "r"(addr) : "memory");
}
__device__ __forceinline__ void ldsm4t(uint32_t* r, uint32_t addr) {
    asm volatile("ldmatrix.sync.aligned.m8n8.x4.trans.shared.b16 {%0,%1,%2,%3}, [%4];" : "=r"(r[0]), "=r"(r[1]), "=r"(r[2]), "=r"(r[3]) : "r"(addr) : "memory");
}
__device__ __forceinline__ void ldsm2(uint32_t* r, uint32_t addr) {
    asm volatile("ldmatrix.sync.aligned.m8n8.x2.shared.b16 {%0,%1}, [%2];" : "=r"(r[0]), "=r"(r[1]) : "r"(addr) : "memory");
}
__device__ __forceinline__ void stsm4t(uint32_t addr, uint32_t r0, uint32_t r1, uint32_t r2, uint32_t r3) {
    asm volatile("stmatrix.sync.aligned.m8n8.x4.trans.shared.b16 [%0], {%1,%2,%3,%4};" :: "r"(addr), "r"(r0), "r"(r1), "r"(r2), "r"(r3) : "memory");
}
__device__ __forceinline__ float tanh_ap(float x) { float r; asm("tanh.approx.f32 %0, %1;" : "=f"(r) : "f"(x)); return r; }
__device__ __forceinline__ uint32_t pack_bf16(float lo, float hi) { uint32_t r; asm("cvt.rn.bf16x2.f32 %0, %1, %2;" : "=r"(r) : "f"(hi), "f"(lo)); return r; }
__device__ __forceinline__ uint32_t fma_bf16x2(uint32_t a, uint32_t b, uint32_t c) { uint32_t r; asm("fma.rn.bf16x2 %0, %1, %2, %3;" : "=r"(r) : "r"(a), "r"(b), "r"(c)); return r; }
__device__ __forceinline__ uint32_t mul_bf16x2(uint32_t a, uint32_t b) { uint32_t r; asm("mul.rn.bf16x2 %0, %1, %2;" : "=r"(r) : "r"(a), "r"(b)); return r; }
__device__ __forceinline__ uint32_t seteq_bf16x2(uint32_t a, uint32_t b) { uint32_t r; asm("set.eq.bf16x2.bf16x2 %0, %1, %2;" : "=r"(r) : "r"(a), "r"(b)); return r; }
__device__ __forceinline__ uint32_t prmt(uint32_t a, uint32_t b, uint32_t s) { uint32_t r; asm("prmt.b32 %0, %1, %2, %3;" : "=r"(r) : "r"(a), "r"(b), "r"(s)); return r; }
__device__ __forceinline__ uint32_t shl_clamp(uint32_t a, uint32_t s) { uint32_t r; asm("shl.b32 %0, %1, %2;" : "=r"(r) : "r"(a), "r"(s)); return r; }
__device__ __forceinline__ void cp16(uint32_t dst, const void* src) { asm volatile("cp.async.cg.shared.global [%0], [%1], 16;" :: "r"(dst), "l"(src) : "memory"); }
__device__ __forceinline__ void cp16z(uint32_t dst, const void* src, uint32_t sz) { asm volatile("cp.async.cg.shared.global [%0], [%1], 16, %2;" :: "r"(dst), "l"(src), "r"(sz) : "memory"); }
__device__ __forceinline__ const void* madw(uint32_t a, uint32_t m, const void* base) {
    const void* r; asm("mad.wide.u32 %0, %1, %2, %3;" : "=l"(r) : "r"(a), "r"(m), "l"(base)); return r;
}
__device__ __forceinline__ void cp16_p(bool p, uint32_t dst, const void* src) {
    asm volatile("{\n.reg .pred p;\nsetp.ne.u32 p, %2, 0;\n@p cp.async.cg.shared.global [%0], [%1], 16;\n}" :: "r"(dst), "l"(src), "r"((uint32_t)p) : "memory");
}
__device__ __forceinline__ void cp_commit() { asm volatile("cp.async.commit_group;" ::: "memory"); }
template <int N> __device__ __forceinline__ void cp_wait() { asm volatile("cp.async.wait_group %0;" :: "n"(N) : "memory"); }
__device__ __forceinline__ uint4 lds128(uint32_t a) { uint4 v; asm volatile("ld.shared.v4.u32 {%0,%1,%2,%3}, [%4];" : "=r"(v.x), "=r"(v.y), "=r"(v.z), "=r"(v.w) : "r"(a) : "memory"); return v; }
__device__ __forceinline__ uint2 lds64(uint32_t a) { uint2 v; asm volatile("ld.shared.v2.u32 {%0,%1}, [%2];" : "=r"(v.x), "=r"(v.y) : "r"(a) : "memory"); return v; }
__device__ __forceinline__ uint32_t lds32(uint32_t a) { uint32_t v; asm volatile("ld.shared.u32 %0, [%1];" : "=r"(v) : "r"(a) : "memory"); return v; }
__device__ __forceinline__ uint32_t lds8(uint32_t a) { uint32_t v; asm volatile("ld.shared.u8 %0, [%1];" : "=r"(v) : "r"(a) : "memory"); return v; }
__device__ __forceinline__ void sts32(uint32_t a, uint32_t v) { asm volatile("st.shared.u32 [%0], %1;" :: "r"(a), "r"(v) : "memory"); }
__device__ __forceinline__ void sts8(uint32_t a, uint32_t v) { asm volatile("st.shared.u8 [%0], %1;" :: "r"(a), "r"(v) : "memory"); }
__device__ __forceinline__ void sts128(uint32_t a, uint4 v) { asm volatile("st.shared.v4.u32 [%0], {%1,%2,%3,%4};" :: "r"(a), "r"(v.x), "r"(v.y), "r"(v.z), "r"(v.w) : "memory"); }
__device__ __forceinline__ uint32_t atoms_add(uint32_t a, uint32_t v) { uint32_t r; asm volatile("atom.shared.add.u32 %0, [%1], %2;" : "=r"(r) : "r"(a), "r"(v) : "memory"); return r; }
__device__ __forceinline__ void reds_add(uint32_t a, uint32_t v) { asm volatile("red.shared.add.u32 [%0], %1;" :: "r"(a), "r"(v) : "memory"); }
__device__ __forceinline__ uint32_t atoms_add_p(bool p, uint32_t a, uint32_t v) {
    uint32_t r = 0;
    asm volatile("{\n.reg .pred p;\nsetp.ne.u32 p, %3, 0;\n@p atom.shared.add.u32 %0, [%1], %2;\n}" : "+r"(r) : "r"(a), "r"(v), "r"((uint32_t)p) : "memory");
    return r;
}
__device__ __forceinline__ uint32_t lds32_p(bool p, uint32_t a) {
    uint32_t r = 0;
    asm volatile("{\n.reg .pred p;\nsetp.ne.u32 p, %2, 0;\n@p ld.shared.u32 %0, [%1];\n}" : "+r"(r) : "r"(a), "r"((uint32_t)p) : "memory");
    return r;
}
__device__ __forceinline__ void sts32_p(bool p, uint32_t a, uint32_t v) {
    asm volatile("{\n.reg .pred p;\nsetp.ne.u32 p, %2, 0;\n@p st.shared.u32 [%0], %1;\n}" :: "r"(a), "r"(v), "r"((uint32_t)p) : "memory");
}
__device__ __forceinline__ void sts8_p(bool p, uint32_t a, uint32_t v) {
    asm volatile("{\n.reg .pred p;\nsetp.ne.u32 p, %2, 0;\n@p st.shared.u8 [%0], %1;\n}" :: "r"(a), "r"(v), "r"((uint32_t)p) : "memory");
}
__device__ __forceinline__ void st_piece(uint4* p, uint4 v) {
    asm volatile("{\n.reg .b128 q;\n.reg .b64 lo, hi;\nmov.b64 lo, {%1,%2};\nmov.b64 hi, {%3,%4};\nmov.b128 q, {lo, hi};\nst.relaxed.gpu.global.b128 [%0], q;\n}"
                 :: "l"(p), "r"(v.x), "r"(v.y), "r"(v.z), "r"(v.w) : "memory");
}
__device__ __forceinline__ uint4 ld_piece(const uint4* p) {
    uint4 v;
    asm volatile("{\n.reg .b128 q;\n.reg .b64 lo, hi;\nld.relaxed.gpu.global.b128 q, [%4];\nmov.b128 {lo, hi}, q;\nmov.b64 {%0,%1}, lo;\nmov.b64 {%2,%3}, hi;\n}"
                 : "=r"(v.x), "=r"(v.y), "=r"(v.z), "=r"(v.w) : "l"(p) : "memory");
    return v;
}
__device__ __forceinline__ void mbar_init(uint32_t bar, uint32_t cnt) { asm volatile("mbarrier.init.shared::cta.b64 [%0], %1;" :: "r"(bar), "r"(cnt) : "memory"); }
__device__ __forceinline__ void mbar_expect(uint32_t bar, uint32_t bytes) { asm volatile("mbarrier.arrive.expect_tx.shared::cta.b64 _, [%0], %1;" :: "r"(bar), "r"(bytes) : "memory"); }
__device__ __forceinline__ void mbar_wait(uint32_t bar, uint32_t parity) {
    uint32_t ok; int it = 0;
    do {
        asm volatile("{\n.reg .pred p;\nmbarrier.try_wait.parity.shared::cta.b64 p, [%1], %2;\nselp.u32 %0, 1, 0, p;\n}" : "=r"(ok) : "r"(bar), "r"(parity) : "memory");
    } while (!ok && ++it < (1 << 22));
}
__device__ __forceinline__ void tma_load2d(uint32_t dst, const CUtensorMap* tm, int c0, int c1, uint32_t bar) {
    asm volatile("cp.async.bulk.tensor.2d.shared::cluster.global.mbarrier::complete_tx::bytes [%0], [%1, {%3, %4}], [%2];"
                 :: "r"(dst), "l"(tm), "r"(bar), "r"(c0), "r"(c1) : "memory");
}
__device__ __forceinline__ void tma_load2d_mc(uint32_t dst, const CUtensorMap* tm, int c0, int c1, uint32_t bar) {
    asm volatile("cp.async.bulk.tensor.2d.shared::cluster.global.mbarrier::complete_tx::bytes.multicast::cluster [%0], [%1, {%3, %4}], [%2], %5;"
                 :: "r"(dst), "l"(tm), "r"(bar), "r"(c0), "r"(c1), "h"((uint16_t)3) : "memory");
}
__device__ __forceinline__ void tma_store2d(const CUtensorMap* tm, int c0, int c1, uint32_t src) {
    asm volatile("cp.async.bulk.tensor.2d.global.shared::cta.bulk_group [%0, {%2, %3}], [%1];"
                 :: "l"(tm), "r"(src), "r"(c0), "r"(c1) : "memory");
}
__device__ __forceinline__ void spin(uint32_t cycles) {
    uint32_t c0, c1;
    asm volatile("mov.u32 %0, %%clock;" : "=r"(c0));
    do { asm volatile("mov.u32 %0, %%clock;" : "=r"(c1)); } while (c1 - c0 < cycles);
}
__device__ __forceinline__ void lt_bar() { asm volatile("bar.sync 3, 256;" ::: "memory"); }
__device__ __forceinline__ void wg_bar(int id) { asm volatile("bar.sync %0, 128;" :: "r"(id) : "memory"); }

__device__ __forceinline__ void wgmma_n80(float (&d)[40], uint64_t da, uint64_t db, int acc) {
    asm volatile("{\n.reg .pred p;\nsetp.ne.b32 p, %42, 0;\n"
        "wgmma.mma_async.sync.aligned.m64n80k16.f32.bf16.bf16 "
        "{%0,%1,%2,%3,%4,%5,%6,%7,%8,%9,%10,%11,%12,%13,%14,%15,%16,%17,%18,%19,"
        "%20,%21,%22,%23,%24,%25,%26,%27,%28,%29,%30,%31,%32,%33,%34,%35,%36,%37,%38,%39}, "
        "%40, %41, p, 1, 1, 1, 0;\n}\n"
        : "+f"(d[0]), "+f"(d[1]), "+f"(d[2]), "+f"(d[3]), "+f"(d[4]), "+f"(d[5]), "+f"(d[6]), "+f"(d[7]), "+f"(d[8]), "+f"(d[9]),
          "+f"(d[10]), "+f"(d[11]), "+f"(d[12]), "+f"(d[13]), "+f"(d[14]), "+f"(d[15]), "+f"(d[16]), "+f"(d[17]), "+f"(d[18]), "+f"(d[19]),
          "+f"(d[20]), "+f"(d[21]), "+f"(d[22]), "+f"(d[23]), "+f"(d[24]), "+f"(d[25]), "+f"(d[26]), "+f"(d[27]), "+f"(d[28]), "+f"(d[29]),
          "+f"(d[30]), "+f"(d[31]), "+f"(d[32]), "+f"(d[33]), "+f"(d[34]), "+f"(d[35]), "+f"(d[36]), "+f"(d[37]), "+f"(d[38]), "+f"(d[39])
        : "l"(da), "l"(db), "r"(acc));
}

__device__ __forceinline__ void gemm_issue(float (&d)[40], uint32_t wbase, uint32_t xbase) {
    asm volatile("wgmma.fence.sync.aligned;" ::: "memory");
#pragma unroll
    for (int s = 0; s < 8; s++) {
        const uint32_t aa = wbase + s * 2048, ab = xbase + (s >> 2) * 10240 + (s & 3) * 32;
        const uint64_t da = (uint64_t)((aa & 0x3FFFF) >> 4) | ((uint64_t)64 << 16) | ((uint64_t)64 << 32) | ((uint64_t)1 << 62);
        const uint64_t db = (uint64_t)((ab & 0x3FFFF) >> 4) | ((uint64_t)1 << 16) | ((uint64_t)64 << 32) | ((uint64_t)1 << 62);
        wgmma_n80(d, da, db, s > 0);
    }
    asm volatile("wgmma.commit_group.sync.aligned;" ::: "memory");
}
__device__ __forceinline__ void gemm_wait(float (&d)[40]) {
    asm volatile("wgmma.wait_group.sync.aligned 0;" ::: "memory");
#pragma unroll
    for (int i = 0; i < 40; i++) asm volatile("" : "+f"(d[i]) :: "memory");
}
__device__ __forceinline__ void gemm_store(const float (&d)[40], float sc, uint32_t base, int w4, int lane) {
    const int mi = lane >> 3, rr = lane & 7;
    const uint32_t sa = base + (rr + 8 * (mi >> 1)) * 128 + (((2 * w4 + (mi & 1)) ^ rr) << 4);
#pragma unroll
    for (int p = 0; p < 5; p++) {
        const float* q = d + 8 * p;
        stsm4t(sa + p * 2048, pack_bf16(q[0] * sc, q[1] * sc), pack_bf16(q[2] * sc, q[3] * sc),
               pack_bf16(q[4] * sc, q[5] * sc), pack_bf16(q[6] * sc, q[7] * sc));
    }
}

struct Params {
    const int* dst;
    const int* src;
    unsigned* bar;
    uint4* xch;
    const bf16* gw;
    const bf16* e_attr;
    const char* table;
    bf16* out;
};

__global__ void __launch_bounds__(NTHR, 1)
egc_kernel(const Params p, const __grid_constant__ CUtensorMap tm_x, const __grid_constant__ CUtensorMap tm_g,
           const __grid_constant__ CUtensorMap tm_u, const __grid_constant__ CUtensorMap tm_v, const __grid_constant__ CUtensorMap tm_t) {
    extern __shared__ unsigned char smem_raw[];
    const uint32_t sb = ((uint32_t)__cvta_generic_to_shared(smem_raw) + 1023u) & ~1023u;
    const int tid = threadIdx.x, lane = tid & 31, b = blockIdx.x;
    const int w = __shfl_sync(0xffffffffu, tid >> 5, 0);
    const int wq = w >> 2, w4 = w & 3;
    const int g = lane >> 2, t = lane & 3, mi = lane >> 3, rr = lane & 7;
    TRACE(0);

    uint32_t Cf[8][4];
    auto load_cf = [&]() {
        const int krow = rr + 8 * (mi >> 1);
#pragma unroll
        for (int j = 0; j < 8; j++) {
            const int c = 2 * j + (mi & 1);
            ldsm4t(Cf[j], sb + SM_C + krow * 256 + ((c & 8) << 4) + (((c & 7) ^ rr) << 4));
#pragma unroll
            for (int q = 0; q < 4; q++) Cf[j][q] = mul_bf16x2(Cf[j][q], 0x3F003F00u);
        }
    };
    uint32_t xAf[8][2];
    float agg[8][4];
    const uint32_t ident = (g == 2 * t) ? 0x3F80u : ((g == 2 * t + 1) ? 0x3F800000u : 0u);
    const int nslot = (w < 12) ? 5 : 4;
    auto load_node_frags = [&]() {
        const int mynode = lds8(sb + SM_TNODE + w * 8 + ((rr < nslot) ? rr : 0));
#pragma unroll
        for (int jp = 0; jp < 4; jp++) {
            const int c = 4 * jp + mi;
            const uint32_t off = mynode * 128 + (((c & 7) ^ (mynode & 7)) << 4);
            uint32_t q[4];
            ldsm4t(q, sb + SM_WA + (c >> 3) * 16384 + off);
            xAf[2 * jp][0] = q[0]; xAf[2 * jp][1] = q[1]; xAf[2 * jp + 1][0] = q[2]; xAf[2 * jp + 1][1] = q[3];
            ldsm4t(q, sb + SM_X + (c >> 3) * 10240 + off);
            mma1688_z(agg[2 * jp], q[0], q[1], ident);
            mma1688_z(agg[2 * jp + 1], q[2], q[3], ident);
        }
    };
    uint32_t bar_target = 0;
    constexpr int LT = 256;
    if (wq < 2) {
        uint32_t epoch = 0;
        {
            const int r = tid >> 4, c = tid & 15;
            cp16(sb + SM_C + r * 256 + ((c & 8) << 4) + (((c & 7) ^ (r & 7)) << 4), p.gw + (256 + r) * 128 + c * 8);
            cp_commit();
        }
        if (tid == 0) {
            asm volatile("ld.relaxed.gpu.global.u32 %0, [%1];" : "=r"(epoch) : "l"(p.bar) : "memory");
            for (int i = 0; i < 9; i++) mbar_init(sb + SM_BAR + i * 8, 1);
            asm volatile("fence.mbarrier_init.release.cluster;" ::: "memory");
            const uint32_t bx = sb + SM_BAR;
            mbar_expect(bx, 20480);
#pragma unroll
            for (int i = 0; i < 8; i++) mbar_expect(bx + 8 + i * 8, 16384);
            spin(START_DELAY);
            tma_load2d(sb + SM_X, &tm_x, 0, b * NPC, bx);
            tma_load2d(sb + SM_X + 10240, &tm_x, 64, b * NPC, bx);
            tma_load2d(sb + SM_R0, &tm_g, 0, 128, bx + 8);
            tma_load2d(sb + SM_R0 + 16384, &tm_g, 64, 128, bx + 16);
            tma_load2d(sb + SM_R0 + 2 * 16384, &tm_v, 0, 0, bx + 24);
            tma_load2d(sb + SM_R0 + 3 * 16384, &tm_v, 64, 0, bx + 32);
        }
        cp_wait<0>();
        asm volatile("bar.sync 6, 256;" ::: "memory");
        asm volatile("bar.arrive 8, 512;" ::: "memory");
        TRACE(1);
        load_cf();
        float d[40];
        const uint32_t xt = sb + SM_X;
        const bool elect = (w4 == 0 && lane == 0);
        mbar_wait(sb + SM_BAR, 0);
#pragma unroll 1
        for (int r = 0; r < 4; r++) {
            const uint32_t wt = sb + ((r < 2) ? SM_R0 + r * 32768 : ((r == 2) ? SM_WA : SM_WU)) + wq * 16384;
            mbar_wait(sb + SM_BAR + 8 + (2 * r + wq) * 8, 0);
            TRACE(2 + 2 * r);
            gemm_issue(d, wt, xt);
            if (r == 0 && tid == 0) {
#pragma unroll
                for (int i = 0; i < 2; i++) {
                    tma_load2d(sb + SM_WA + i * 16384, &tm_g, i * 64, 0, sb + SM_BAR + 8 + (4 + i) * 8);
                    tma_load2d(sb + SM_WU + i * 16384, &tm_u, i * 64, 0, sb + SM_BAR + 8 + (6 + i) * 8);
                }
            }
            if (r == 2) {
                asm volatile("bar.sync 4, 512;" ::: "memory");
                if (elect) {
                    asm volatile("cp.async.bulk.wait_group 0;" ::: "memory");
                    asm volatile("fence.proxy.async.global;" ::: "memory");
                    asm volatile("red.relaxed.gpu.global.add.u32 [%0], 1;" :: "l"(p.bar) : "memory");
                }
            }
            if (r == 3 && tid == 0) {
                const int e0 = b * ECH, ne = min(ECH, EE - e0);
                asm volatile("cp.async.bulk.prefetch.L2.global [%0], %1;" :: "l"(p.e_attr + (size_t)e0 * 16), "r"(ne * 32) : "memory");
            }
            __syncwarp();
            gemm_wait(d);
            if (r < 3) wg_bar(1 + wq); else asm volatile("bar.sync 6, 256;" ::: "memory");
            gemm_store(d, (r == 1) ? 0.25f : 0.5f, (r < 3) ? wt : xt + wq * 10240, w4, lane);
            if (r < 2) {
                asm volatile("fence.proxy.async.shared::cta;" ::: "memory");
                wg_bar(1 + wq);
                if (elect) {
                    tma_store2d(&tm_t, (2 * r + wq) * 64, b * NPC, wt);
                    asm volatile("cp.async.bulk.commit_group;" ::: "memory");
                }
                __syncwarp();
            }
            TRACE(3 + 2 * r);
        }

        bar_target = (epoch / (2 * NCTA) + 1) * (2 * NCTA);
        TRACE(9);
    } else {
        const int lt = tid - LT;
        int ed[5], es[5];
        uint32_t epoch = 0;
        {
            const int e4 = b * ECH + 4 * lt, e1 = b * ECH + 1024 + lt;
            const bool ok4 = e4 < EE, ok1 = (lt < ECH - 1024) && (e1 < EE);
            const int4 d4 = ok4 ? __ldg((const int4*)(p.dst + e4)) : make_int4(-1, -1, -1, -1);
            ed[4] = ok1 ? __ldg(p.dst + e1) : -1;
            const int4 s4 = ok4 ? __ldg((const int4*)(p.src + e4)) : make_int4(0, 0, 0, 0);
            es[4] = ok1 ? __ldg(p.src + e1) : 0;
            ed[0] = d4.x; ed[1] = d4.y; ed[2] = d4.z; ed[3] = d4.w;
            es[0] = s4.x; es[1] = s4.y; es[2] = s4.z; es[3] = s4.w;
        }
        if (lt == 0) asm volatile("ld.relaxed.gpu.global.u32 %0, [%1];" : "=r"(epoch) : "l"(p.bar) : "memory");
        if (lt < 136) sts32(sb + SM_HIST + lt * 4, 0);
        if (lt < 128) { sts32(sb + SM_KEYS + lt * 4, 0); sts32(sb + SM_TDEG + lt * 4, 0); }
        if (lt < 64) sts32(sb + SM_DBIN + lt * 4, 0);
        if (lt == 0) sts32(sb + SM_FLAG, 0);
        lt_bar();
        TRACE(24);
        {
            uint32_t jj[5], rk[5];
#pragma unroll
            for (int m = 0; m < 5; m++) {
                jj[m] = (ed[m] >= 0) ? (((uint32_t)ed[m] * 55189u) >> 22) : (132 + (lane & 3));
                rk[m] = atoms_add(sb + SM_HIST + jj[m] * 4, 1);
            }
#pragma unroll
            for (int m = 0; m < 5; m++) {
                const uint32_t loc = (uint32_t)ed[m] - jj[m] * NPC;
                const uint32_t q = (rk[m] * 43691u) >> 17;
                const uint32_t off = jj[m] * (PIECES * 16) + q * 16 + (rk[m] - 3 * q + 1) * 4;
                sts32(sb + SM_S + ((ed[m] >= 0 && rk[m] < XCAP) ? off : NCTA * PIECES * 16 + lane * 4),
                      (uint32_t)es[m] | (loc << 14) | ((uint32_t)((m < 4) ? 4 * lt + m : 1024 + lt) << 21));
            }
        }
        if (lt == 0) sts32(sb + SM_FLAG + 4, epoch / (2 * NCTA));
        TRACE(25);
        lt_bar();
        const uint32_t bar_q = lds32(sb + SM_FLAG + 4);
        epoch = (bar_q + 1) & 0xFFFFFF;
        {
            uint4 v[6]; uint32_t c[6];
#pragma unroll
            for (int m = 0; m < 6; m++) {
                const int pc = min(lt + m * LT, NCTA * PIECES - 1);
                v[m] = lds128(sb + SM_S + pc * 16);
                c[m] = lds32(sb + SM_HIST + ((pc * 6554) >> 16) * 4);
            }
#pragma unroll
            for (int m = 0; m < 6; m++) {
                const int pc = lt + m * LT;
                const int j = (pc * 6554) >> 16, q = pc - j * PIECES;
                if ((m < 5 || pc < NCTA * PIECES) && (q < 4 || c[m] > 3 * (q & ~1) || b >= 128)) {
                    v[m].x = (epoch << 8) | min(c[m], 255u);
                    st_piece(p.xch + (((j * (PIECES / 2) + (q >> 1)) * NCTA + b) * 2 + (q & 1)), v[m]);
                }
            }
        }
        TRACE(46);
        asm volatile("bar.arrive 4, 512;" ::: "memory");
        lt_bar();
        if (lt == 0) asm volatile("red.relaxed.gpu.global.add.u32 [%0], 1;" :: "l"(p.bar + 1) : "memory");
        asm volatile("bar.sync 8, 512;" ::: "memory");
        load_cf();
        if (lt == 0) {
            uint32_t v; int it = 0;
            const uint32_t target = bar_q * NCTA + NCTA * 17 / 20;
            do { asm volatile("ld.relaxed.gpu.global.u32 %0, [%1];" : "=r"(v) : "l"(p.bar + 1) : "memory"); }
            while ((int)(v - target) < 0 && ++it < SPIN_LIMIT);
        }
        lt_bar();
        TRACE(26);
        uint4 pv[6];
        const int pi5 = 128 + ((lt >> 1) & 3), pq5 = 2 * (lt >> 3) + (lt & 1);
        const uint4* px0 = p.xch + b * (NCTA * PIECES) + lt;
        const uint4* px5 = p.xch + b * (NCTA * PIECES) + (lt >> 3) * (2 * NCTA) + 256 + (lt & 7);
        const uint32_t tg = epoch << 8;
        auto fetch = [&](const uint4* a) {
            uint4 v = ld_piece(a);
            int it = 0;
            while (((v.x ^ tg) >> 8) && ++it < SPIN_LIMIT) { __nanosleep(100); v = ld_piece(a); }
            return v;
        };
        pv[0] = ld_piece(px0);
        pv[1] = ld_piece(px0 + 2 * NCTA);
        pv[5] = (lt < 4 * PIECES) ? ld_piece(px5) : make_uint4(tg, 0, 0, 0);
        for (int it = 0; (((pv[0].x ^ tg) | (pv[1].x ^ tg) | (pv[5].x ^ tg)) >> 8) && it < SPIN_LIMIT; it++) {
            __nanosleep(100);
            if ((pv[0].x ^ tg) >> 8) pv[0] = ld_piece(px0);
            if ((pv[1].x ^ tg) >> 8) pv[1] = ld_piece(px0 + 2 * NCTA);
            if ((pv[5].x ^ tg) >> 8) pv[5] = ld_piece(px5);
        }
        const int cnt = pv[0].x & 255, cnt5 = pv[5].x & 255;
#pragma unroll
        for (int m = 2; m < 5; m++) pv[m] = (cnt > 6 * m) ? ld_piece(px0 + m * (2 * NCTA)) : make_uint4(tg, 0, 0, 0);
        if (cnt > XCAP || cnt5 > XCAP) sts32(sb + SM_FLAG, 1);
        TRACE(27);
        const uint32_t dmy = (96 + lane) * 4;
        uint32_t ao[9], rk[9];
        auto count = [&](int m, int o) {
            const int nv = (m < 5) ? cnt - 3 * (2 * m + (lt & 1)) : cnt5 - 3 * pq5;
#pragma unroll
            for (int s = 0; s < 3; s++) {
                const uint32_t pl = (s == 0) ? pv[m].y : ((s == 1) ? pv[m].z : pv[m].w);
                ao[o + s] = (nv > s) ? ((pl >> 12) & 0x1FC) : dmy;
                rk[o + s] = atoms_add(sb + SM_KEYS + ao[o + s], 1);
            }
        };
        auto put = [&](int m, int o) {
            const uint32_t e0s = (uint32_t)(((m < 5) ? (lt >> 1) : pi5) * ECH) << 14;
#pragma unroll
            for (int s = 0; s < 3; s++) {
                const uint32_t pl = (s == 0) ? pv[m].y : ((s == 1) ? pv[m].z : pv[m].w);
                const bool ok = ao[o + s] < 96 * 4 && rk[o + s] < NCAP;
                sts32(sb + SM_NL + (ok ? ao[o + s] * NCAP + rk[o + s] * 4 : NPC * NCAP * 4 + lane * 4), (pl & 0x3FFF) + ((pl >> 21) << 14) + e0s);
            }
        };
        count(0, 0);
        count(1, 3);
        const bool has5 = lt < 64;
        if (has5) count(5, 6);
        put(0, 0);
        put(1, 3);
        if (has5) put(5, 6);
        if (((pv[2].x ^ tg) | (pv[3].x ^ tg) | (pv[4].x ^ tg)) >> 8) {
#pragma unroll
            for (int m = 2; m < 5; m++) if (cnt > 6 * m) pv[m] = fetch(px0 + m * (2 * NCTA));
        }
#pragma unroll
        for (int m = 2; m < 5; m++) {
            if (__any_sync(0xffffffffu, cnt > 6 * m)) { count(m, 0); put(m, 0); }
        }
        TRACE(28);
        lt_bar();
        if (lt < 96) {
            const uint32_t deg = (lt < NPC) ? lds32(sb + SM_KEYS + lt * 4) : 0;
            const uint32_t bin = 63 - min(deg, 63u);
            const uint32_t r0 = atoms_add_p(lt < NPC, sb + SM_DBIN + bin * 4, 1);
            if (deg > NCAP) sts32(sb + SM_FLAG, 1);
            asm volatile("bar.sync 5, 96;" ::: "memory");
            const uint2 c2 = lds64(sb + SM_DBIN + lane * 8);
            uint32_t inc = c2.x + c2.y;
#pragma unroll
            for (int o = 1; o < 32; o <<= 1) { const uint32_t u = __shfl_up_sync(0xffffffffu, inc, o); if (lane >= o) inc += u; }
            const uint32_t ex = inc - c2.x - c2.y;
            const uint32_t pe = __shfl_sync(0xffffffffu, ex, bin >> 1), p0 = __shfl_sync(0xffffffffu, c2.x, bin >> 1);
            const int rank = pe + ((bin & 1) ? p0 : 0) + r0;
            const int k = rank >> 4, pos = rank & 15;
            const int tile = (k == 4) ? 11 - pos : ((pos < 4) ? 12 + ((k & 1) ? 3 - pos : pos) : ((k < 3) ? pos - 4 : 15 - pos));
            if (lt < NPC) {
                sts32(sb + SM_TDEG + (tile * 8 + k) * 4, deg);
                sts8(sb + SM_TNODE + tile * 8 + k, lt);
            }
        }
        TRACE(29);
        TRACE(30);
    }
    TRACE(31);
    __syncthreads();
    TRACE(32);
    bool slow = lds32(sb + SM_FLAG) != 0;

    constexpr uint32_t RD = SM_R1 - SM_R0;
    const uint32_t ring0 = sb + SM_R0 + w * STAGE;
    const char* tab_l = p.table + lane * 16;
    asm volatile("" : "+l"(tab_l));
    const char* e_l = (const char*)p.e_attr + (mi & 1) * 16;
    asm volatile("" : "+l"(e_l));
    const uint32_t cpo = lane * 16;
    const uint32_t elo = 4096 + rr * 32 + (((mi & 1) ^ ((rr >> 2) & 1)) << 4);
    const uint32_t lsrc = sb + SM_LSE + w * TCAP * 4, lid = sb + SM_LID + w * TCAP;
    const uint32_t lec = rr * 4;

    auto issue_full = [&](uint32_t lp, uint32_t dl) {
        const uint4 s0 = lds128(lp), s1 = lds128(lp + 16);
        const uint32_t eo = lds32(lp + lec);
        const uint32_t sv[8] = {s0.x, s0.y, s0.z, s0.w, s1.x, s1.y, s1.z, s1.w};
#pragma unroll
        for (int j = 0; j < 8; j++) cp16(ring0 + dl + (cpo ^ (j << 4)) + j * 512, madw(sv[j] & 0x3FFF, 512, tab_l));
        cp16(ring0 + dl + elo, madw(eo >> 14, 32, e_l));
    };
    auto issue0 = [&]() {
        const int cnt = lds32(sb + SM_TCNT + w * 4), nit = (cnt + 7) >> 3;
        if (nit > 0) {
            const int pad = nit * 8 - cnt;
            const uint4 s0 = lds128(lsrc), s1 = lds128(lsrc + 16);
            const uint32_t eo = lds32(lsrc + lec);
            const uint32_t sv[8] = {s0.x, s0.y, s0.z, s0.w, s1.x, s1.y, s1.z, s1.w};
#pragma unroll
            for (int j = 0; j < 8; j++) cp16z(ring0 + (cpo ^ (j << 4)) + j * 512, madw(sv[j] & 0x3FFF, 512, tab_l), (j >= pad) ? 16 : 0);
            cp16z(ring0 + elo, madw(eo >> 14, 32, e_l), (rr >= pad) ? 16 : 0);
        }
        cp_commit();
    };
    auto issue1 = [&]() {
        if ((int)lds32(sb + SM_TCNT + w * 4) > 8) issue_full(lsrc + 32, RD);
        cp_commit();
    };
    uint32_t bar_v = 0;
    bool over = false;
    if (tid == 0) asm volatile("ld.relaxed.gpu.global.u32 %0, [%1];" : "=r"(bar_v) : "l"(p.bar) : "memory");
    if (!slow) {
        const uint2 tn = lds64(sb + SM_TNODE + w * 8);
        const uint4 dg = lds128(sb + SM_TDEG + w * 32);
        const uint32_t p1 = dg.x, p2 = p1 + dg.y, p3 = p2 + dg.z, p4 = p3 + dg.w, tot = p4 + lds32(sb + SM_TDEG + w * 32 + 16);
        const uint32_t pad = (0u - tot) & 7u;
        if (lane == 0) sts32(sb + SM_TCNT + w * 4, tot);
        over = tot + pad > TCAP;
        uint32_t wd[TCAP / 32], sl[TCAP / 32];
#pragma unroll
        for (int r = 0; r < TCAP / 32; r++) {
            const uint32_t q = lane + 32 * r - pad;
            sl[r] = (q >= p1) + (q >= p2) + (q >= p3) + (q >= p4);
            const uint32_t pre = (q >= p4) ? p4 : ((q >= p3) ? p3 : ((q >= p2) ? p2 : ((q >= p1) ? p1 : 0)));
            const uint32_t node = prmt(tn.x, tn.y, sl[r]) & 0xFF;
            wd[r] = lds32(sb + SM_NL + ((q < tot) ? (node * NCAP + q - pre) * 4 : 0));
        }
#pragma unroll
        for (int r = 0; r < TCAP / 32; r++) {
            const uint32_t q = lane + 32 * r - pad;
            sts32(lsrc + (lane + 32 * r) * 4, (q < tot) ? wd[r] : 0);
            sts8(lid + lane + 32 * r, (q < tot) ? sl[r] * 16 : 0x7F);
        }
    }
    TRACE(10);
    if (tid == 0) {
        int it = 0;
        while ((int)(bar_v - bar_target) < 0 && ++it < SPIN_LIMIT)
            asm volatile("ld.relaxed.gpu.global.u32 %0, [%1];" : "=r"(bar_v) : "l"(p.bar) : "memory");
    }
    slow = __syncthreads_or(slow || over);
    TRACE(11);
    if (!slow) {
        issue0();
        issue1();
    } else {
        if (tid < NPC) sts8(sb + SM_TNODE + (tid & 15) * 8 + (tid >> 4), tid);
        __syncthreads();
    }
    TRACE(33);
    load_node_frags();
    TRACE(34);

    const uint32_t ldo = rr * 512 + ((mi ^ rr) << 4);
    const uint32_t sel = (g | ((8 | g) << 4) | (g << 8) | ((8 | g) << 12)) |
                         (((2 * t) | ((8 | (2 * t)) << 4) | ((2 * t + 1) << 8) | ((8 | (2 * t + 1)) << 12)) << 16);
    const uint32_t gg = (g * 16) | ((g * 16) << 16);
    const uint32_t tt = (t * 32) | ((t * 32 + 16) << 16);

    auto compute = [&](uint32_t st, uint32_t idp) {
        uint32_t eb[2];
        ldsm2(eb, st + elo);
        const uint2 iw = lds64(idp);
        const uint32_t sx = seteq_bf16x2(prmt(iw.x, iw.y, sel), tt);
        const uint32_t sa = seteq_bf16x2(prmt(iw.x, iw.y, sel >> 16), gg);
#pragma unroll
        for (int jj = 0; jj < 4; jj++) {
            uint32_t xb[4], hv[4];
            const uint32_t la = st + (ldo ^ ((jj & 1) << 6)) + (jj >> 1) * 128;
            ldsm4(xb, la);
            ldsm4t(hv, la + 256);
#pragma unroll
            for (int u = 0; u < 2; u++) {
                const int j = 2 * jj + u;
                float d[4];
                mma16816_z(d, Cf[j][0], Cf[j][1], Cf[j][2], Cf[j][3], eb[0], eb[1]);
                mma1688(d, xAf[j][0], xAf[j][1], sx);
                mma16816(d, ident, 0u, 0u, ident, xb[2 * u], xb[2 * u + 1]);
                const uint32_t m0 = fma_bf16x2(pack_bf16(tanh_ap(d[0]), tanh_ap(d[1])), hv[2 * u], hv[2 * u]);
                const uint32_t m1 = fma_bf16x2(pack_bf16(tanh_ap(d[2]), tanh_ap(d[3])), hv[2 * u + 1], hv[2 * u + 1]);
                mma1688(agg[j], m0, m1, sa);
            }
        }
    };

    const int nseg = slow ? NSEG : 1;
#pragma unroll 1
    for (int seg = 0; seg < nseg; seg++) {
        if (slow) {
            __syncthreads();
            if (tid < 16) sts32(sb + SM_TCNT + tid * 4, 0);
            __syncthreads();
            const int e = seg * TCAP + tid;
            int loc = -1; uint32_t r = 0;
            if (tid < TCAP && e < EE) {
                const int dd = __ldg(p.dst + e) - b * NPC;
                if (dd >= 0 && dd < NPC) { loc = dd; r = atoms_add(sb + SM_TCNT + (loc & 15) * 4, 1); }
            }
            __syncthreads();
            if (loc >= 0) {
                const uint32_t tile = loc & 15, tot = lds32(sb + SM_TCNT + tile * 4);
                const uint32_t pos = tile * TCAP + ((0u - tot) & 7u) + r;
                sts32(sb + SM_LSE + pos * 4, (uint32_t)__ldg(p.src + e) | ((uint32_t)e << 14));
                sts8(sb + SM_LID + pos, (loc >> 4) << 4);
            }
            const int pad = (0 - (int)lds32(sb + SM_TCNT + w * 4)) & 7;
            if (lane < pad) { sts8(sb + SM_LID + w * TCAP + lane, 0x7F); sts32(sb + SM_LSE + (w * TCAP + lane) * 4, 0); }
            __syncthreads();
            issue0();
            issue1();
        }
        const int nit = __shfl_sync(0xffffffffu, ((int)lds32(sb + SM_TCNT + w * 4) + 7) >> 3, 0);
        uint32_t st = ring0, so = ring0 + RD, lp = lsrc + 32, idp = lid;
        const uint32_t lend = lsrc + nit * 32;
        constexpr int AVG_NIT = (EE + NCTA * 128 - 1) / (NCTA * 128);
        constexpr int HEAVY = EE / NN * NPC * 207 / 200;
        const int ctot = __reduce_add_sync(0xffffffffu, (lane < 16) ? (int)lds32(sb + SM_TCNT + lane * 4) : 0);
        if (nit <= AVG_NIT && ctot <= HEAVY) {
#pragma unroll 1
            for (; lp <= lend; lp += 32, idp += 8) {
                if (idp == lid) cp_wait<1>(); else cp_wait<0>();
                __syncwarp();
                if (idp != lid && lp < lend) issue_full(lp, so - ring0);
                cp_commit();
                compute(st, idp);
                const uint32_t tmp = st; st = so; so = tmp;
            }
        } else {
#pragma unroll 1
            for (; lp <= lend; lp += 32, idp += 8) {
                cp_wait<1>();
                __syncwarp();
                compute(st, idp);
                __syncwarp();
                if (lp + 32 < lend) issue_full(lp + 32, st - ring0);
                cp_commit();
                const uint32_t tmp = st; st = so; so = tmp;
            }
        }
        cp_wait<0>();
        __syncwarp();
    }
    TRACE(35);

    {
        uint32_t o[8][2];
#pragma unroll
        for (int j = 0; j < 8; j++) {
            float v[4];
#pragma unroll
            for (int q = 0; q < 4; q++) { const float h = agg[j][q]; v[q] = fmaf(h, tanh_ap(h), h); }
            o[j][0] = pack_bf16(v[0], v[1]); o[j][1] = pack_bf16(v[2], v[3]);
        }
#pragma unroll
        for (int jp = 0; jp < 4; jp++) {
            const int c = 4 * jp + mi;
            stsm4t(ring0 + rr * 256 + ((c & 8) << 4) + (((c & 7) ^ rr) << 4), o[2 * jp][0], o[2 * jp][1], o[2 * jp + 1][0], o[2 * jp + 1][1]);
        }
        __syncwarp();
#pragma unroll
        for (int i = 0; i < 3; i++) {
            const int idx = lane + 32 * i, row = idx >> 4, c = idx & 15;
            const int nd = b * NPC + (int)lds8(sb + SM_TNODE + w * 8 + (row & 7));
            if (row < nslot && nd < NN) {
                const uint4 v = lds128(ring0 + row * 256 + ((c & 8) << 4) + (((c & 7) ^ row) << 4));
                *(uint4*)((char*)p.out + (size_t)nd * 256 + c * 16) = v;
            }
        }
    }
    TRACE(36);
}

__device__ __align__(16) bf16 g_fb_xa[NN * 128];
__device__ __align__(16) float g_fb_h[NN * 128];

__global__ void fb_node_kernel(const bf16* x, const bf16* uw, const bf16* vw, const bf16* gw, bf16* table) {
    __shared__ float xs[128];
    const int n = blockIdx.x, f = threadIdx.x;
    xs[f] = __bfloat162float(x[n * 128 + f]);
    __syncthreads();
    float a = 0.f, bb = 0.f, v = 0.f, u = 0.f;
    for (int k = 0; k < 128; k++) {
        const float xv = xs[k];
        a += xv * __bfloat162float(gw[k * 128 + f]);
        bb += xv * __bfloat162float(gw[(128 + k) * 128 + f]);
        v += xv * __bfloat162float(vw[k * 128 + f]);
        u += xv * __bfloat162float(uw[k * 128 + f]);
    }
    table[n * 256 + f] = __float2bfloat16(0.5f * bb);
    table[n * 256 + 128 + f] = __float2bfloat16(0.25f * v);
    g_fb_xa[n * 128 + f] = __float2bfloat16(0.5f * a);
    g_fb_h[n * 128 + f] = 0.5f * u;
}
__global__ void fb_edge_kernel(const bf16* e_attr, const int* src, const int* dst, const bf16* gw, const bf16* table) {
    const int e = blockIdx.x, f = threadIdx.x, s = src[e], d = dst[e];
    float z = 0.f;
    for (int k = 0; k < 16; k++) z += __bfloat162float(e_attr[e * 16 + k]) * __bfloat162float(gw[(256 + k) * 128 + f]);
    z = 0.5f * z + __bfloat162float(g_fb_xa[d * 128 + f]) + __bfloat162float(table[s * 256 + f]);
    const float hv = __bfloat162float(table[s * 256 + 128 + f]);
    atomicAdd(&g_fb_h[d * 128 + f], fmaf(hv, tanhf(z), hv));
}
__global__ void fb_out_kernel(bf16* out) {
    const int i = blockIdx.x * 128 + threadIdx.x;
    const float h = g_fb_h[i];
    out[i] = __float2bfloat16(fmaf(h, tanhf(h), h));
}

typedef CUresult (*EncodeFn)(CUtensorMap*, CUtensorMapDataType, cuuint32_t, void*, const cuuint64_t*, const cuuint64_t*,
                             const cuuint32_t*, const cuuint32_t*, CUtensorMapInterleave, CUtensorMapSwizzle,
                             CUtensorMapL2promotion, CUtensorMapFloatOOBfill);

static void make_map(EncodeFn enc, CUtensorMap* tm, const void* base, int rows, int cols, int box_rows) {
    cuuint64_t dims[2] = {(cuuint64_t)cols, (cuuint64_t)rows};
    cuuint64_t strides[1] = {(cuuint64_t)cols * 2};
    cuuint32_t box[2] = {64, (cuuint32_t)box_rows};
    cuuint32_t es[2] = {1, 1};
    enc(tm, CU_TENSOR_MAP_DATA_TYPE_BFLOAT16, 2, (void*)base, dims, strides, box, es, CU_TENSOR_MAP_INTERLEAVE_NONE,
        CU_TENSOR_MAP_SWIZZLE_128B, CU_TENSOR_MAP_L2_PROMOTION_NONE, CU_TENSOR_MAP_FLOAT_OOB_FILL_NONE);
}

}

extern "C" void kernel_launch(void* const* d_in, const int* in_sizes, int n_in, void* d_out, int out_size) {
    using namespace egc;
    (void)in_sizes; (void)n_in; (void)out_size;
    static EncodeFn enc = nullptr;
    static void* table = nullptr;
    static void* xch = nullptr;
    static void* bar = nullptr;
    static bool persistent = false;
    if (!enc) {
        void* fn = nullptr;
        cudaDriverEntryPointQueryResult qr;
        cudaGetDriverEntryPoint("cuTensorMapEncodeTiled", &fn, cudaEnableDefault, &qr);
        enc = (EncodeFn)fn;
        cudaGetSymbolAddress(&table, g_table);
        cudaGetSymbolAddress(&xch, g_xch);
        cudaGetSymbolAddress(&bar, g_bar);
        cudaFuncSetAttribute(egc_kernel, cudaFuncAttributeMaxDynamicSharedMemorySize, SMEM_BYTES);
        int dev = 0, sms = 0, per_sm = 0;
        cudaGetDevice(&dev);
        cudaDeviceGetAttribute(&sms, cudaDevAttrMultiProcessorCount, dev);
        cudaOccupancyMaxActiveBlocksPerMultiprocessor(&per_sm, egc_kernel, NTHR, SMEM_BYTES);
        persistent = enc != nullptr && sms * per_sm >= NCTA;
    }
    if (!persistent) {
        const bf16* x = (const bf16*)d_in[0];
        fb_node_kernel<<<NN, 128, 0, cudaStreamPerThread>>>(x, (const bf16*)d_in[4], (const bf16*)d_in[5], (const bf16*)d_in[6], (bf16*)table);
        fb_edge_kernel<<<EE, 128, 0, cudaStreamPerThread>>>((const bf16*)d_in[1], (const int*)d_in[2], (const int*)d_in[3], (const bf16*)d_in[6], (const bf16*)table);
        fb_out_kernel<<<NN, 128, 0, cudaStreamPerThread>>>((bf16*)d_out);
        return;
    }
    CUtensorMap tm_x, tm_g, tm_u, tm_v, tm_t;
    make_map(enc, &tm_x, d_in[0], NN, 128, 80);
    make_map(enc, &tm_u, d_in[4], 128, 128, 128);
    make_map(enc, &tm_v, d_in[5], 128, 128, 128);
    make_map(enc, &tm_g, d_in[6], 272, 128, 128);
    make_map(enc, &tm_t, table, NN, 256, NPC);
    Params p;
    p.e_attr = (const bf16*)d_in[1];
    p.src = (const int*)d_in[2];
    p.dst = (const int*)d_in[3];
    p.gw = (const bf16*)d_in[6];
    p.out = (bf16*)d_out;
    p.bar = (unsigned*)bar;
    p.xch = (uint4*)xch;
    p.table = (const char*)table;
    egc_kernel<<<NCTA, NTHR, SMEM_BYTES, cudaStreamPerThread>>>(p, tm_x, tm_g, tm_u, tm_v, tm_t);
}
```

```cpp
#include <cuda_runtime.h>
#include <cuda_bf16.h>
#include <cuda.h>
#include <stdint.h>

namespace egc {

typedef __nv_bfloat16 bf16;

constexpr int NN = 10000, EE = 160000;
constexpr int NCTA = 132, NPC = 76, ECH = 1216, NTHR = 512;
constexpr int PIECES = 10, XCAP = 3 * PIECES;
constexpr int TCAP = 96;
constexpr int NSEG = (EE + TCAP - 1) / TCAP;
constexpr int SPIN_LIMIT = 1 << 20;
constexpr uint32_t START_DELAY = 420;

constexpr int STAGE = 4352;
constexpr int SM_R0 = 0;
constexpr int SM_R1 = 16 * STAGE;
constexpr int SM_S = SM_R1;
constexpr int SM_WU = SM_R1 + 8 * STAGE;
constexpr int SM_WA = SM_R1 + 16 * STAGE;
constexpr int SM_X = SM_WA + 32768;
constexpr int SM_C = SM_X + 20480;
constexpr int SM_LSE = SM_C + 4096;
constexpr int SM_LID = SM_LSE + 6144;
constexpr int SM_HIST = SM_LID + 1536;
constexpr int SM_KEYS = SM_HIST + 544;
constexpr int SM_DBIN = SM_KEYS + 512;
constexpr int SM_TDEG = SM_DBIN + 256;
constexpr int SM_TNODE = SM_TDEG + 512;
constexpr int SM_TCNT = SM_TNODE + 128;
constexpr int SM_FLAG = SM_TCNT + 64;
constexpr int NCAP = 40;
constexpr int SM_NL = SM_FLAG + 16;
constexpr int SM_BAR = SM_NL + NPC * NCAP * 4 + 128;
constexpr int SM_END = SM_BAR + 9 * 8;
constexpr int SMEM_BYTES = SM_END + 1024;
static_assert(SM_R1 % 1024 == 0 && SM_WU % 1024 == 0 && SM_WA % 1024 == 0 && SM_X % 1024 == 0 && SM_BAR % 8 == 0 && SM_TDEG % 16 == 0 &&
              SM_LSE % 16 == 0 && SM_LID % 8 == 0 && SM_DBIN % 8 == 0 && SM_TNODE % 8 == 0 && SMEM_BYTES <= 232448, "shared memory map");

__device__ __align__(1024) uint4 g_table[NN * 32];
__device__ __align__(1024) uint4 g_xch[NCTA * NCTA * PIECES];
__device__ __align__(128) unsigned g_bar[32];

__device__ __forceinline__ void mma16816(float* d, uint32_t a0, uint32_t a1, uint32_t a2, uint32_t a3, uint32_t b0, uint32_t b1) {
    asm("mma.sync.aligned.m16n8k16.row.col.f32.bf16.bf16.f32 {%0,%1,%2,%3}, {%4,%5,%6,%7}, {%8,%9}, {%0,%1,%2,%3};"
        : "+f"(d[0]), "+f"(d[1]), "+f"(d[2]), "+f"(d[3]) : "r"(a0), "r"(a1), "r"(a2), "r"(a3), "r"(b0), "r"(b1));
}
__device__ __forceinline__ void mma16816_z(float* d, uint32_t a0, uint32_t a1, uint32_t a2, uint32_t a3, uint32_t b0, uint32_t b1) {
    asm("mma.sync.aligned.m16n8k16.row.col.f32.bf16.bf16.f32 {%0,%1,%2,%3}, {%4,%5,%6,%7}, {%8,%9}, {%10,%10,%10,%10};"
        : "=f"(d[0]), "=f"(d[1]), "=f"(d[2]), "=f"(d[3]) : "r"(a0), "r"(a1), "r"(a2), "r"(a3), "r"(b0), "r"(b1), "f"(0.f));
}
__device__ __forceinline__ void mma1688(float* d, uint32_t a0, uint32_t a1, uint32_t b0) {
    asm("mma.sync.aligned.m16n8k8.row.col.f32.bf16.bf16.f32 {%0,%1,%2,%3}, {%4,%5}, {%6}, {%0,%1,%2,%3};"
        : "+f"(d[0]), "+f"(d[1]), "+f"(d[2]), "+f"(d[3]) : "r"(a0), "r"(a1), "r"(b0));
}
__device__ __forceinline__ void mma1688_z(float* d, uint32_t a0, uint32_t a1, uint32_t b0) {
    asm("mma.sync.aligned.m16n8k8.row.col.f32.bf16.bf16.f32 {%0,%1,%2,%3}, {%4,%5}, {%6}, {%7,%7,%7,%7};"
        : "=f"(d[0]), "=f"(d[1]), "=f"(d[2]), "=f"(d[3]) : "r"(a0), "r"(a1), "r"(b0), "f"(0.f));
}
__device__ __forceinline__ void ldsm4(uint32_t* r, uint32_t addr) {
    asm volatile("ldmatrix.sync.aligned.m8n8.x4.shared.b16 {%0,%1,%2,%3}, [%4];" : "=r"(r[0]), "=r"(r[1]), "=r"(r[2]), "=r"(r[3]) : "r"(addr) : "memory");
}
__device__ __forceinline__ void ldsm4t(uint32_t* r, uint32_t addr) {
    asm volatile("ldmatrix.sync.aligned.m8n8.x4.trans.shared.b16 {%0,%1,%2,%3}, [%4];" : "=r"(r[0]), "=r"(r[1]), "=r"(r[2]), "=r"(r[3]) : "r"(addr) : "memory");
}
__device__ __forceinline__ void ldsm2(uint32_t* r, uint32_t addr) {
    asm volatile("ldmatrix.sync.aligned.m8n8.x2.shared.b16 {%0,%1}, [%2];" : "=r"(r[0]), "=r"(r[1]) : "r"(addr) : "memory");
}
__device__ __forceinline__ void stsm4t(uint32_t addr, uint32_t r0, uint32_t r1, uint32_t r2, uint32_t r3) {
    asm volatile("stmatrix.sync.aligned.m8n8.x4.trans.shared.b16 [%0], {%1,%2,%3,%4};" :: "r"(addr), "r"(r0), "r"(r1), "r"(r2), "r"(r3) : "memory");
}
__device__ __forceinline__ float tanh_ap(float x) { float r; asm("tanh.approx.f32 %0, %1;" : "=f"(r) : "f"(x)); return r; }
__device__ __forceinline__ uint32_t pack_bf16(float lo, float hi) { uint32_t r; asm("cvt.rn.bf16x2.f32 %0, %1, %2;" : "=r"(r) : "f"(hi), "f"(lo)); return r; }
__device__ __forceinline__ uint32_t fma_bf16x2(uint32_t a, uint32_t b, uint32_t c) { uint32_t r; asm("fma.rn.bf16x2 %0, %1, %2, %3;" : "=r"(r) : "r"(a), "r"(b), "r"(c)); return r; }
__device__ __forceinline__ uint32_t mul_bf16x2(uint32_t a, uint32_t b) { uint32_t r; asm("mul.rn.bf16x2 %0, %1, %2;" : "=r"(r) : "r"(a), "r"(b)); return r; }
__device__ __forceinline__ uint32_t seteq_bf16x2(uint32_t a, uint32_t b) { uint32_t r; asm("set.eq.bf16x2.bf16x2 %0, %1, %2;" : "=r"(r) : "r"(a), "r"(b)); return r; }
__device__ __forceinline__ uint32_t prmt(uint32_t a, uint32_t b, uint32_t s) { uint32_t r; asm("prmt.b32 %0, %1, %2, %3;" : "=r"(r) : "r"(a), "r"(b), "r"(s)); return r; }
__device__ __forceinline__ void cp16(uint32_t dst, const void* src) { asm volatile("cp.async.cg.shared.global [%0], [%1], 16;" :: "r"(dst), "l"(src) : "memory"); }
__device__ __forceinline__ void cp16z(uint32_t dst, const void* src, uint32_t sz) { asm volatile("cp.async.cg.shared.global [%0], [%1], 16, %2;" :: "r"(dst), "l"(src), "r"(sz) : "memory"); }
__device__ __forceinline__ const void* madw(uint32_t a, uint32_t m, const void* base) {
    const void* r; asm("mad.wide.u32 %0, %1, %2, %3;" : "=l"(r) : "r"(a), "r"(m), "l"(base)); return r;
}
__device__ __forceinline__ void cp_commit() { asm volatile("cp.async.commit_group;" ::: "memory"); }
template <int N> __device__ __forceinline__ void cp_wait() { asm volatile("cp.async.wait_group %0;" :: "n"(N) : "memory"); }
__device__ __forceinline__ uint4 lds128(uint32_t a) { uint4 v; asm volatile("ld.shared.v4.u32 {%0,%1,%2,%3}, [%4];" : "=r"(v.x), "=r"(v.y), "=r"(v.z), "=r"(v.w) : "r"(a) : "memory"); return v; }
__device__ __forceinline__ uint2 lds64(uint32_t a) { uint2 v; asm volatile("ld.shared.v2.u32 {%0,%1}, [%2];" : "=r"(v.x), "=r"(v.y) : "r"(a) : "memory"); return v; }
__device__ __forceinline__ uint32_t lds32(uint32_t a) { uint32_t v; asm volatile("ld.shared.u32 %0, [%1];" : "=r"(v) : "r"(a) : "memory"); return v; }
__device__ __forceinline__ uint32_t lds8(uint32_t a) { uint32_t v; asm volatile("ld.shared.u8 %0, [%1];" : "=r"(v) : "r"(a) : "memory"); return v; }
__device__ __forceinline__ void sts32(uint32_t a, uint32_t v) { asm volatile("st.shared.u32 [%0], %1;" :: "r"(a), "r"(v) : "memory"); }
__device__ __forceinline__ void sts8(uint32_t a, uint32_t v) { asm volatile("st.shared.u8 [%0], %1;" :: "r"(a), "r"(v) : "memory"); }
__device__ __forceinline__ uint32_t atoms_add(uint32_t a, uint32_t v) { uint32_t r; asm volatile("atom.shared.add.u32 %0, [%1], %2;" : "=r"(r) : "r"(a), "r"(v) : "memory"); return r; }
__device__ __forceinline__ uint32_t atoms_add_p(bool p, uint32_t a, uint32_t v) {
    uint32_t r = 0;
    asm volatile("{\n.reg .pred p;\nsetp.ne.u32 p, %3, 0;\n@p atom.shared.add.u32 %0, [%1], %2;\n}" : "+r"(r) : "r"(a), "r"(v), "r"((uint32_t)p) : "memory");
    return r;
}
__device__ __forceinline__ void st_piece(uint4* p, uint4 v) {
    asm volatile("{\n.reg .b128 q;\n.reg .b64 lo, hi;\nmov.b64 lo, {%1,%2};\nmov.b64 hi, {%3,%4};\nmov.b128 q, {lo, hi};\nst.relaxed.gpu.global.b128 [%0], q;\n}"
                 :: "l"(p), "r"(v.x), "r"(v.y), "r"(v.z), "r"(v.w) : "memory");
}
__device__ __forceinline__ uint4 ld_piece(const uint4* p) {
    uint4 v;
    asm volatile("{\n.reg .b128 q;\n.reg .b64 lo, hi;\nld.relaxed.gpu.global.b128 q, [%4];\nmov.b128 {lo, hi}, q;\nmov.b64 {%0,%1}, lo;\nmov.b64 {%2,%3}, hi;\n}"
                 : "=r"(v.x), "=r"(v.y), "=r"(v.z), "=r"(v.w) : "l"(p) : "memory");
    return v;
}
__device__ __forceinline__ void mbar_init(uint32_t bar, uint32_t cnt) { asm volatile("mbarrier.init.shared::cta.b64 [%0], %1;" :: "r"(bar), "r"(cnt) : "memory"); }
__device__ __forceinline__ void mbar_expect(uint32_t bar, uint32_t bytes) { asm volatile("mbarrier.arrive.expect_tx.shared::cta.b64 _, [%0], %1;" :: "r"(bar), "r"(bytes) : "memory"); }
__device__ __forceinline__ void mbar_wait(uint32_t bar, uint32_t parity) {
    uint32_t ok; int it = 0;
    do {
        asm volatile("{\n.reg .pred p;\nmbarrier.try_wait.parity.shared::cta.b64 p, [%1], %2;\nselp.u32 %0, 1, 0, p;\n}" : "=r"(ok) : "r"(bar), "r"(parity) : "memory");
    } while (!ok && ++it < (1 << 22));
}
__device__ __forceinline__ void tma_load2d(uint32_t dst, const CUtensorMap* tm, int c0, int c1, uint32_t bar) {
    asm volatile("cp.async.bulk.tensor.2d.shared::cluster.global.mbarrier::complete_tx::bytes [%0], [%1, {%3, %4}], [%2];"
                 :: "r"(dst), "l"(tm), "r"(bar), "r"(c0), "r"(c1) : "memory");
}
__device__ __forceinline__ void tma_store2d(const CUtensorMap* tm, int c0, int c1, uint32_t src) {
    asm volatile("cp.async.bulk.tensor.2d.global.shared::cta.bulk_group [%0, {%2, %3}], [%1];"
                 :: "l"(tm), "r"(src), "r"(c0), "r"(c1) : "memory");
}
__device__ __forceinline__ void spin(uint32_t cycles) {
    uint32_t c0, c1;
    asm volatile("mov.u32 %0, %%clock;" : "=r"(c0));
    do { asm volatile("mov.u32 %0, %%clock;" : "=r"(c1)); } while (c1 - c0 < cycles);
}
__device__ __forceinline__ void lt_bar() { asm volatile("bar.sync 3, 256;" ::: "memory"); }
__device__ __forceinline__ void wg_bar(int id) { asm volatile("bar.sync %0, 128;" :: "r"(id) : "memory"); }

__device__ __forceinline__ void wgmma_n80(float (&d)[40], uint64_t da, uint64_t db, int acc) {
    asm volatile("{\n.reg .pred p;\nsetp.ne.b32 p, %42, 0;\n"
        "wgmma.mma_async.sync.aligned.m64n80k16.f32.bf16.bf16 "
        "{%0,%1,%2,%3,%4,%5,%6,%7,%8,%9,%10,%11,%12,%13,%14,%15,%16,%17,%18,%19,"
        "%20,%21,%22,%23,%24,%25,%26,%27,%28,%29,%30,%31,%32,%33,%34,%35,%36,%37,%38,%39}, "
        "%40, %41, p, 1, 1, 1, 0;\n}\n"
        : "+f"(d[0]), "+f"(d[1]), "+f"(d[2]), "+f"(d[3]), "+f"(d[4]), "+f"(d[5]), "+f"(d[6]), "+f"(d[7]), "+f"(d[8]), "+f"(d[9]),
          "+f"(d[10]), "+f"(d[11]), "+f"(d[12]), "+f"(d[13]), "+f"(d[14]), "+f"(d[15]), "+f"(d[16]), "+f"(d[17]), "+f"(d[18]), "+f"(d[19]),
          "+f"(d[20]), "+f"(d[21]), "+f"(d[22]), "+f"(d[23]), "+f"(d[24]), "+f"(d[25]), "+f"(d[26]), "+f"(d[27]), "+f"(d[28]), "+f"(d[29]),
          "+f"(d[30]), "+f"(d[31]), "+f"(d[32]), "+f"(d[33]), "+f"(d[34]), "+f"(d[35]), "+f"(d[36]), "+f"(d[37]), "+f"(d[38]), "+f"(d[39])
        : "l"(da), "l"(db), "r"(acc));
}

__device__ __forceinline__ void gemm_issue(float (&d)[40], uint32_t wbase, uint32_t xbase) {
    asm volatile("wgmma.fence.sync.aligned;" ::: "memory");
#pragma unroll
    for (int s = 0; s < 8; s++) {
        const uint32_t aa = wbase + s * 2048, ab = xbase + (s >> 2) * 10240 + (s & 3) * 32;
        const uint64_t da = (uint64_t)((aa & 0x3FFFF) >> 4) | ((uint64_t)64 << 16) | ((uint64_t)64 << 32) | ((uint64_t)1 << 62);
        const uint64_t db = (uint64_t)((ab & 0x3FFFF) >> 4) | ((uint64_t)1 << 16) | ((uint64_t)64 << 32) | ((uint64_t)1 << 62);
        wgmma_n80(d, da, db, s > 0);
    }
    asm volatile("wgmma.commit_group.sync.aligned;" ::: "memory");
}
__device__ __forceinline__ void gemm_wait(float (&d)[40]) {
    asm volatile("wgmma.wait_group.sync.aligned 0;" ::: "memory");
#pragma unroll
    for (int i = 0; i < 40; i++) asm volatile("" : "+f"(d[i]) :: "memory");
}
__device__ __forceinline__ void gemm_store(const float (&d)[40], float sc, uint32_t base, int w4, int lane) {
    const int mi = lane >> 3, rr = lane & 7;
    const uint32_t sa = base + (rr + 8 * (mi >> 1)) * 128 + (((2 * w4 + (mi & 1)) ^ rr) << 4);
#pragma unroll
    for (int p = 0; p < 5; p++) {
        const float* q = d + 8 * p;
        stsm4t(sa + p * 2048, pack_bf16(q[0] * sc, q[1] * sc), pack_bf16(q[2] * sc, q[3] * sc),
               pack_bf16(q[4] * sc, q[5] * sc), pack_bf16(q[6] * sc, q[7] * sc));
    }
}

struct Params {
    const int* dst;
    const int* src;
    unsigned* bar;
    uint4* xch;
    const bf16* gw;
    const bf16* e_attr;
    const char* table;
    bf16* out;
};

__global__ void __launch_bounds__(NTHR, 1)
egc_kernel(const Params p, const __grid_constant__ CUtensorMap tm_x, const __grid_constant__ CUtensorMap tm_g,
           const __grid_constant__ CUtensorMap tm_u, const __grid_constant__ CUtensorMap tm_v, const __grid_constant__ CUtensorMap tm_t) {
    extern __shared__ unsigned char smem_raw[];
    const uint32_t sb = ((uint32_t)__cvta_generic_to_shared(smem_raw) + 1023u) & ~1023u;
    const int tid = threadIdx.x, lane = tid & 31, b = blockIdx.x;
    const int w = __shfl_sync(0xffffffffu, tid >> 5, 0);
    const int wq = w >> 2, w4 = w & 3;
    const int g = lane >> 2, t = lane & 3, mi = lane >> 3, rr = lane & 7;

    uint32_t Cf[8][4];
    auto load_cf = [&]() {
        const int krow = rr + 8 * (mi >> 1);
#pragma unroll
        for (int j = 0; j < 8; j++) {
            const int c = 2 * j + (mi & 1);
            ldsm4t(Cf[j], sb + SM_C + krow * 256 + ((c & 8) << 4) + (((c & 7) ^ rr) << 4));
#pragma unroll
            for (int q = 0; q < 4; q++) Cf[j][q] = mul_bf16x2(Cf[j][q], 0x3F003F00u);
        }
    };
    uint32_t xAf[8][2];
    float agg[8][4];
    const uint32_t ident = (g == 2 * t) ? 0x3F80u : ((g == 2 * t + 1) ? 0x3F800000u : 0u);
    const int nslot = (w < 12) ? 5 : 4;
    auto load_node_frags = [&]() {
        const int mynode = lds8(sb + SM_TNODE + w * 8 + ((rr < nslot) ? rr : 0));
#pragma unroll
        for (int jp = 0; jp < 4; jp++) {
            const int c = 4 * jp + mi;
            const uint32_t off = mynode * 128 + (((c & 7) ^ (mynode & 7)) << 4);
            uint32_t q[4];
            ldsm4t(q, sb + SM_WA + (c >> 3) * 16384 + off);
            xAf[2 * jp][0] = q[0]; xAf[2 * jp][1] = q[1]; xAf[2 * jp + 1][0] = q[2]; xAf[2 * jp + 1][1] = q[3];
            ldsm4t(q, sb + SM_X + (c >> 3) * 10240 + off);
            mma1688_z(agg[2 * jp], q[0], q[1], ident);
            mma1688_z(agg[2 * jp + 1], q[2], q[3], ident);
        }
    };
    uint32_t bar_target = 0;
    constexpr int LT = 256;
    if (wq < 2) {
        uint32_t epoch = 0;
        {
            const int r = tid >> 4, c = tid & 15;
            cp16(sb + SM_C + r * 256 + ((c & 8) << 4) + (((c & 7) ^ (r & 7)) << 4), p.gw + (256 + r) * 128 + c * 8);
            cp_commit();
        }
        if (tid == 0) {
            asm volatile("ld.relaxed.gpu.global.u32 %0, [%1];" : "=r"(epoch) : "l"(p.bar) : "memory");
            for (int i = 0; i < 9; i++) mbar_init(sb + SM_BAR + i * 8, 1);
            asm volatile("fence.mbarrier_init.release.cluster;" ::: "memory");
            const uint32_t bx = sb + SM_BAR;
            mbar_expect(bx, 20480);
#pragma unroll
            for (int i = 0; i < 8; i++) mbar_expect(bx + 8 + i * 8, 16384);
            spin(START_DELAY);
            tma_load2d(sb + SM_X, &tm_x, 0, b * NPC, bx);
            tma_load2d(sb + SM_X + 10240, &tm_x, 64, b * NPC, bx);
            tma_load2d(sb + SM_R0, &tm_g, 0, 128, bx + 8);
            tma_load2d(sb + SM_R0 + 16384, &tm_g, 64, 128, bx + 16);
            tma_load2d(sb + SM_R0 + 2 * 16384, &tm_v, 0, 0, bx + 24);
            tma_load2d(sb + SM_R0 + 3 * 16384, &tm_v, 64, 0, bx + 32);
        }
        cp_wait<0>();
        asm volatile("bar.sync 6, 256;" ::: "memory");
        asm volatile("bar.arrive 8, 512;" ::: "memory");
        load_cf();
        float d[40];
        const uint32_t xt = sb + SM_X;
        const bool elect = (w4 == 0 && lane == 0);
        mbar_wait(sb + SM_BAR, 0);
#pragma unroll 1
        for (int r = 0; r < 4; r++) {
            const uint32_t wt = sb + ((r < 2) ? SM_R0 + r * 32768 : ((r == 2) ? SM_WA : SM_WU)) + wq * 16384;
            mbar_wait(sb + SM_BAR + 8 + (2 * r + wq) * 8, 0);
            gemm_issue(d, wt, xt);
            if (r == 0 && tid == 0) {
#pragma unroll
                for (int i = 0; i < 2; i++) {
                    tma_load2d(sb + SM_WA + i * 16384, &tm_g, i * 64, 0, sb + SM_BAR + 8 + (4 + i) * 8);
                    tma_load2d(sb + SM_WU + i * 16384, &tm_u, i * 64, 0, sb + SM_BAR + 8 + (6 + i) * 8);
                }
            }
            if (r == 2) {
                asm volatile("bar.sync 4, 512;" ::: "memory");
                if (elect) {
                    asm volatile("cp.async.bulk.wait_group 0;" ::: "memory");
                    asm volatile("fence.proxy.async.global;" ::: "memory");
                    asm volatile("red.relaxed.gpu.global.add.u32 [%0], 1;" :: "l"(p.bar) : "memory");
                }
            }
            if (r == 3 && tid == 0) {
                const int e0 = b * ECH, ne = min(ECH, EE - e0);
                asm volatile("cp.async.bulk.prefetch.L2.global [%0], %1;" :: "l"(p.e_attr + (size_t)e0 * 16), "r"(ne * 32) : "memory");
            }
            __syncwarp();
            gemm_wait(d);
            if (r < 3) wg_bar(1 + wq); else asm volatile("bar.sync 6, 256;" ::: "memory");
            gemm_store(d, (r == 1) ? 0.25f : 0.5f, (r < 3) ? wt : xt + wq * 10240, w4, lane);
            if (r < 2) {
                asm volatile("fence.proxy.async.shared::cta;" ::: "memory");
                wg_bar(1 + wq);
                if (elect) {
                    tma_store2d(&tm_t, (2 * r + wq) * 64, b * NPC, wt);
                    asm volatile("cp.async.bulk.commit_group;" ::: "memory");
                }
                __syncwarp();
            }
        }

        bar_target = (epoch / (2 * NCTA) + 1) * (2 * NCTA);
    } else {
        const int lt = tid - LT;
        int ed[5], es[5];
        uint32_t epoch = 0;
        {
            const int e4 = b * ECH + 4 * lt, e1 = b * ECH + 1024 + lt;
            const bool ok4 = e4 < EE, ok1 = (lt < ECH - 1024) && (e1 < EE);
            const int4 d4 = ok4 ? __ldg((const int4*)(p.dst + e4)) : make_int4(-1, -1, -1, -1);
            ed[4] = ok1 ? __ldg(p.dst + e1) : -1;
            const int4 s4 = ok4 ? __ldg((const int4*)(p.src + e4)) : make_int4(0, 0, 0, 0);
            es[4] = ok1 ? __ldg(p.src + e1) : 0;
            ed[0] = d4.x; ed[1] = d4.y; ed[2] = d4.z; ed[3] = d4.w;
            es[0] = s4.x; es[1] = s4.y; es[2] = s4.z; es[3] = s4.w;
        }
        if (lt == 0) asm volatile("ld.relaxed.gpu.global.u32 %0, [%1];" : "=r"(epoch) : "l"(p.bar) : "memory");
        if (lt < 136) sts32(sb + SM_HIST + lt * 4, 0);
        if (lt < 128) { sts32(sb + SM_KEYS + lt * 4, 0); sts32(sb + SM_TDEG + lt * 4, 0); }
        if (lt < 64) sts32(sb + SM_DBIN + lt * 4, 0);
        if (lt == 0) sts32(sb + SM_FLAG, 0);
        lt_bar();
        {
            uint32_t jj[5], rk[5];
#pragma unroll
            for (int m = 0; m < 5; m++) {
                jj[m] = (ed[m] >= 0) ? (((uint32_t)ed[m] * 55189u) >> 22) : (132 + (lane & 3));
                rk[m] = atoms_add(sb + SM_HIST + jj[m] * 4, 1);
            }
#pragma unroll
            for (int m = 0; m < 5; m++) {
                const uint32_t loc = (uint32_t)ed[m] - jj[m] * NPC;
                const uint32_t q = (rk[m] * 43691u) >> 17;
                const uint32_t off = jj[m] * (PIECES * 16) + q * 16 + (rk[m] - 3 * q + 1) * 4;
                sts32(sb + SM_S + ((ed[m] >= 0 && rk[m] < XCAP) ? off : NCTA * PIECES * 16 + lane * 4),
                      (uint32_t)es[m] | (loc << 14) | ((uint32_t)((m < 4) ? 4 * lt + m : 1024 + lt) << 21));
            }
        }
        if (lt == 0) sts32(sb + SM_FLAG + 4, epoch / (2 * NCTA));
        lt_bar();
        const uint32_t bar_q = lds32(sb + SM_FLAG + 4);
        epoch = (bar_q + 1) & 0xFFFFFF;
        {
            uint4 v[6]; uint32_t c[6];
#pragma unroll
            for (int m = 0; m < 6; m++) {
                const int pc = min(lt + m * LT, NCTA * PIECES - 1);
                v[m] = lds128(sb + SM_S + pc * 16);
                c[m] = lds32(sb + SM_HIST + ((pc * 6554) >> 16) * 4);
            }
#pragma unroll
            for (int m = 0; m < 6; m++) {
                const int pc = lt + m * LT;
                const int j = (pc * 6554) >> 16, q = pc - j * PIECES;
                if ((m < 5 || pc < NCTA * PIECES) && (q < 4 || c[m] > 3 * (q & ~1) || b >= 128)) {
                    v[m].x = (epoch << 8) | min(c[m], 255u);
                    st_piece(p.xch + (((j * (PIECES / 2) + (q >> 1)) * NCTA + b) * 2 + (q & 1)), v[m]);
                }
            }
        }
        asm volatile("bar.arrive 4, 512;" ::: "memory");
        lt_bar();
        if (lt == 0) asm volatile("red.relaxed.gpu.global.add.u32 [%0], 1;" :: "l"(p.bar + 1) : "memory");
        asm volatile("bar.sync 8, 512;" ::: "memory");
        load_cf();
        if (lt == 0) {
            uint32_t v; int it = 0;
            const uint32_t target = bar_q * NCTA + NCTA * 17 / 20;
            do { asm volatile("ld.relaxed.gpu.global.u32 %0, [%1];" : "=r"(v) : "l"(p.bar + 1) : "memory"); }
            while ((int)(v - target) < 0 && ++it < SPIN_LIMIT);
        }
        lt_bar();
        uint4 pv[6];
        const int pi5 = 128 + ((lt >> 1) & 3), pq5 = 2 * (lt >> 3) + (lt & 1);
        const uint4* px0 = p.xch + b * (NCTA * PIECES) + lt;
        const uint4* px5 = p.xch + b * (NCTA * PIECES) + (lt >> 3) * (2 * NCTA) + 256 + (lt & 7);
        const uint32_t tg = epoch << 8;
        auto fetch = [&](const uint4* a) {
            uint4 v = ld_piece(a);
            int it = 0;
            while (((v.x ^ tg) >> 8) && ++it < SPIN_LIMIT) { __nanosleep(100); v = ld_piece(a); }
            return v;
        };
        pv[0] = ld_piece(px0);
        pv[1] = ld_piece(px0 + 2 * NCTA);
        pv[5] = (lt < 4 * PIECES) ? ld_piece(px5) : make_uint4(tg, 0, 0, 0);
        for (int it = 0; (((pv[0].x ^ tg) | (pv[1].x ^ tg) | (pv[5].x ^ tg)) >> 8) && it < SPIN_LIMIT; it++) {
            __nanosleep(100);
            if ((pv[0].x ^ tg) >> 8) pv[0] = ld_piece(px0);
            if ((pv[1].x ^ tg) >> 8) pv[1] = ld_piece(px0 + 2 * NCTA);
            if ((pv[5].x ^ tg) >> 8) pv[5] = ld_piece(px5);
        }
        const int cnt = pv[0].x & 255, cnt5 = pv[5].x & 255;
#pragma unroll
        for (int m = 2; m < 5; m++) pv[m] = (cnt > 6 * m) ? ld_piece(px0 + m * (2 * NCTA)) : make_uint4(tg, 0, 0, 0);
        if (cnt > XCAP || cnt5 > XCAP) sts32(sb + SM_FLAG, 1);
        const uint32_t dmy = (96 + lane) * 4;
        uint32_t ao[9], rk[9];
        auto count = [&](int m, int o) {
            const int nv = (m < 5) ? cnt - 3 * (2 * m + (lt & 1)) : cnt5 - 3 * pq5;
#pragma unroll
            for (int s = 0; s < 3; s++) {
                const uint32_t pl = (s == 0) ? pv[m].y : ((s == 1) ? pv[m].z : pv[m].w);
                ao[o + s] = (nv > s) ? ((pl >> 12) & 0x1FC) : dmy;
                rk[o + s] = atoms_add(sb + SM_KEYS + ao[o + s], 1);
            }
        };
        auto put = [&](int m, int o) {
            const uint32_t e0s = (uint32_t)(((m < 5) ? (lt >> 1) : pi5) * ECH) << 14;
#pragma unroll
            for (int s = 0; s < 3; s++) {
                const uint32_t pl = (s == 0) ? pv[m].y : ((s == 1) ? pv[m].z : pv[m].w);
                const bool ok = ao[o + s] < 96 * 4 && rk[o + s] < NCAP;
                sts32(sb + SM_NL + (ok ? ao[o + s] * NCAP + rk[o + s] * 4 : NPC * NCAP * 4 + lane * 4), (pl & 0x3FFF) + ((pl >> 21) << 14) + e0s);
            }
        };
        count(0, 0);
        count(1, 3);
        const bool has5 = lt < 64;
        if (has5) count(5, 6);
        put(0, 0);
        put(1, 3);
        if (has5) put(5, 6);
        if (((pv[2].x ^ tg) | (pv[3].x ^ tg) | (pv[4].x ^ tg)) >> 8) {
#pragma unroll
            for (int m = 2; m < 5; m++) if (cnt > 6 * m) pv[m] = fetch(px0 + m * (2 * NCTA));
        }
#pragma unroll
        for (int m = 2; m < 5; m++) {
            if (__any_sync(0xffffffffu, cnt > 6 * m)) { count(m, 0); put(m, 0); }
        }
        lt_bar();
        if (lt < 96) {
            const uint32_t deg = (lt < NPC) ? lds32(sb + SM_KEYS + lt * 4) : 0;
            const uint32_t bin = 63 - min(deg, 63u);
            const uint32_t r0 = atoms_add_p(lt < NPC, sb + SM_DBIN + bin * 4, 1);
            if (deg > NCAP) sts32(sb + SM_FLAG, 1);
            asm volatile("bar.sync 5, 96;" ::: "memory");
            const uint2 c2 = lds64(sb + SM_DBIN + lane * 8);
            uint32_t inc = c2.x + c2.y;
#pragma unroll
            for (int o = 1; o < 32; o <<= 1) { const uint32_t u = __shfl_up_sync(0xffffffffu, inc, o); if (lane >= o) inc += u; }
            const uint32_t ex = inc - c2.x - c2.y;
            const uint32_t pe = __shfl_sync(0xffffffffu, ex, bin >> 1), p0 = __shfl_sync(0xffffffffu, c2.x, bin >> 1);
            const int rank = pe + ((bin & 1) ? p0 : 0) + r0;
            const int k = rank >> 4, pos = rank & 15;
            const int tile = (k == 4) ? 11 - pos : ((pos < 4) ? 12 + ((k & 1) ? 3 - pos : pos) : ((k < 3) ? pos - 4 : 15 - pos));
            if (lt < NPC) {
                sts32(sb + SM_TDEG + (tile * 8 + k) * 4, deg);
                sts8(sb + SM_TNODE + tile * 8 + k, lt);
            }
        }
    }
    __syncthreads();
    bool slow = lds32(sb + SM_FLAG) != 0;

    constexpr uint32_t RD = SM_R1 - SM_R0;
    const uint32_t ring0 = sb + SM_R0 + w * STAGE;
    const char* tab_l = p.table + lane * 16;
    asm volatile("" : "+l"(tab_l));
    const char* e_l = (const char*)p.e_attr + (mi & 1) * 16;
    asm volatile("" : "+l"(e_l));
    const uint32_t cpo = lane * 16;
    const uint32_t elo = 4096 + rr * 32 + (((mi & 1) ^ ((rr >> 2) & 1)) << 4);
    const uint32_t lsrc = sb + SM_LSE + w * TCAP * 4, lid = sb + SM_LID + w * TCAP;
    const uint32_t lec = rr * 4;

    auto issue_full = [&](uint32_t lp, uint32_t dl) {
        const uint4 s0 = lds128(lp), s1 = lds128(lp + 16);
        const uint32_t eo = lds32(lp + lec);
        const uint32_t sv[8] = {s0.x, s0.y, s0.z, s0.w, s1.x, s1.y, s1.z, s1.w};
#pragma unroll
        for (int j = 0; j < 8; j++) cp16(ring0 + dl + (cpo ^ (j << 4)) + j * 512, madw(sv[j] & 0x3FFF, 512, tab_l));
        cp16(ring0 + dl + elo, madw(eo >> 14, 32, e_l));
    };
    auto issue0 = [&]() {
        const int cnt = lds32(sb + SM_TCNT + w * 4), nit = (cnt + 7) >> 3;
        if (nit > 0) {
            const int pad = nit * 8 - cnt;
            const uint4 s0 = lds128(lsrc), s1 = lds128(lsrc + 16);
            const uint32_t eo = lds32(lsrc + lec);
            const uint32_t sv[8] = {s0.x, s0.y, s0.z, s0.w, s1.x, s1.y, s1.z, s1.w};
#pragma unroll
            for (int j = 0; j < 8; j++) cp16z(ring0 + (cpo ^ (j << 4)) + j * 512, madw(sv[j] & 0x3FFF, 512, tab_l), (j >= pad) ? 16 : 0);
            cp16z(ring0 + elo, madw(eo >> 14, 32, e_l), (rr >= pad) ? 16 : 0);
        }
        cp_commit();
    };
    auto issue1 = [&]() {
        if ((int)lds32(sb + SM_TCNT + w * 4) > 8) issue_full(lsrc + 32, RD);
        cp_commit();
    };
    uint32_t bar_v = 0;
    bool over = false;
    if (tid == 0) asm volatile("ld.relaxed.gpu.global.u32 %0, [%1];" : "=r"(bar_v) : "l"(p.bar) : "memory");
    if (!slow) {
        const uint2 tn = lds64(sb + SM_TNODE + w * 8);
        const uint4 dg = lds128(sb + SM_TDEG + w * 32);
        const uint32_t p1 = dg.x, p2 = p1 + dg.y, p3 = p2 + dg.z, p4 = p3 + dg.w, tot = p4 + lds32(sb + SM_TDEG + w * 32 + 16);
        const uint32_t pad = (0u - tot) & 7u;
        if (lane == 0) sts32(sb + SM_TCNT + w * 4, tot);
        over = tot + pad > TCAP;
        uint32_t wd[TCAP / 32], sl[TCAP / 32];
#pragma unroll
        for (int r = 0; r < TCAP / 32; r++) {
            const uint32_t q = lane + 32 * r - pad;
            sl[r] = (q >= p1) + (q >= p2) + (q >= p3) + (q >= p4);
            const uint32_t pre = (q >= p4) ? p4 : ((q >= p3) ? p3 : ((q >= p2) ? p2 : ((q >= p1) ? p1 : 0)));
            const uint32_t node = prmt(tn.x, tn.y, sl[r]) & 0xFF;
            wd[r] = lds32(sb + SM_NL + ((q < tot) ? (node * NCAP + q - pre) * 4 : 0));
        }
#pragma unroll
        for (int r = 0; r < TCAP / 32; r++) {
            const uint32_t q = lane + 32 * r - pad;
            sts32(lsrc + (lane + 32 * r) * 4, (q < tot) ? wd[r] : 0);
            sts8(lid + lane + 32 * r, (q < tot) ? sl[r] * 16 : 0x7F);
        }
    }
    if (tid == 0) {
        int it = 0;
        while ((int)(bar_v - bar_target) < 0 && ++it < SPIN_LIMIT)
            asm volatile("ld.relaxed.gpu.global.u32 %0, [%1];" : "=r"(bar_v) : "l"(p.bar) : "memory");
    }
    slow = __syncthreads_or(slow || over);
    if (!slow) {
        issue0();
        issue1();
    } else {
        if (tid < NPC) sts8(sb + SM_TNODE + (tid & 15) * 8 + (tid >> 4), tid);
        __syncthreads();
    }
    load_node_frags();

    const uint32_t ldo = rr * 512 + ((mi ^ rr) << 4);
    const uint32_t sel = (g | ((8 | g) << 4) | (g << 8) | ((8 | g) << 12)) |
                         (((2 * t) | ((8 | (2 * t)) << 4) | ((2 * t + 1) << 8) | ((8 | (2 * t + 1)) << 12)) << 16);
    const uint32_t gg = (g * 16) | ((g * 16) << 16);
    const uint32_t tt = (t * 32) | ((t * 32 + 16) << 16);

    auto compute = [&](uint32_t st, uint32_t idp) {
        uint32_t eb[2];
        ldsm2(eb, st + elo);
        const uint2 iw = lds64(idp);
        const uint32_t sx = seteq_bf16x2(prmt(iw.x, iw.y, sel), tt);
        const uint32_t sa = seteq_bf16x2(prmt(iw.x, iw.y, sel >> 16), gg);
#pragma unroll
        for (int jj = 0; jj < 4; jj++) {
            uint32_t xb[4], hv[4];
            const uint32_t la = st + (ldo ^ ((jj & 1) << 6)) + (jj >> 1) * 128;
            ldsm4(xb, la);
            ldsm4t(hv, la + 256);
#pragma unroll
            for (int u = 0; u < 2; u++) {
                const int j = 2 * jj + u;
                float d[4];
                mma16816_z(d, Cf[j][0], Cf[j][1], Cf[j][2], Cf[j][3], eb[0], eb[1]);
                mma1688(d, xAf[j][0], xAf[j][1], sx);
                mma16816(d, ident, 0u, 0u, ident, xb[2 * u], xb[2 * u + 1]);
                const uint32_t m0 = fma_bf16x2(pack_bf16(tanh_ap(d[0]), tanh_ap(d[1])), hv[2 * u], hv[2 * u]);
                const uint32_t m1 = fma_bf16x2(pack_bf16(tanh_ap(d[2]), tanh_ap(d[3])), hv[2 * u + 1], hv[2 * u + 1]);
                mma1688(agg[j], m0, m1, sa);
            }
        }
    };

    const int nseg = slow ? NSEG : 1;
#pragma unroll 1
    for (int seg = 0; seg < nseg; seg++) {
        if (slow) {
            __syncthreads();
            if (tid < 16) sts32(sb + SM_TCNT + tid * 4, 0);
            __syncthreads();
            const int e = seg * TCAP + tid;
            int loc = -1; uint32_t r = 0;
            if (tid < TCAP && e < EE) {
                const int dd = __ldg(p.dst + e) - b * NPC;
                if (dd >= 0 && dd < NPC) { loc = dd; r = atoms_add(sb + SM_TCNT + (loc & 15) * 4, 1); }
            }
            __syncthreads();
            if (loc >= 0) {
                const uint32_t tile = loc & 15, tot = lds32(sb + SM_TCNT + tile * 4);
                const uint32_t pos = tile * TCAP + ((0u - tot) & 7u) + r;
                sts32(sb + SM_LSE + pos * 4, (uint32_t)__ldg(p.src + e) | ((uint32_t)e << 14));
                sts8(sb + SM_LID + pos, (loc >> 4) << 4);
            }
            const int pad = (0 - (int)lds32(sb + SM_TCNT + w * 4)) & 7;
            if (lane < pad) { sts8(sb + SM_LID + w * TCAP + lane, 0x7F); sts32(sb + SM_LSE + (w * TCAP + lane) * 4, 0); }
            __syncthreads();
            issue0();
            issue1();
        }
        const int nit = __shfl_sync(0xffffffffu, ((int)lds32(sb + SM_TCNT + w * 4) + 7) >> 3, 0);
        uint32_t st = ring0, so = ring0 + RD, lp = lsrc + 32, idp = lid;
        const uint32_t lend = lsrc + nit * 32;
        constexpr int AVG_NIT = (EE + NCTA * 128 - 1) / (NCTA * 128);
        constexpr int HEAVY = EE / NN * NPC * 207 / 200;
        const int ctot = __reduce_add_sync(0xffffffffu, (lane < 16) ? (int)lds32(sb + SM_TCNT + lane * 4) : 0);
        if (nit <= AVG_NIT && ctot <= HEAVY) {
#pragma unroll 1
            for (; lp <= lend; lp += 32, idp += 8) {
                if (idp == lid) cp_wait<1>(); else cp_wait<0>();
                __syncwarp();
                if (idp != lid && lp < lend) issue_full(lp, so - ring0);
                cp_commit();
                compute(st, idp);
                const uint32_t tmp = st; st = so; so = tmp;
            }
        } else {
#pragma unroll 1
            for (; lp <= lend; lp += 32, idp += 8) {
                cp_wait<1>();
                __syncwarp();
                compute(st, idp);
                __syncwarp();
                if (lp + 32 < lend) issue_full(lp + 32, st - ring0);
                cp_commit();
                const uint32_t tmp = st; st = so; so = tmp;
            }
        }
        cp_wait<0>();
        __syncwarp();
    }

    {
        uint32_t o[8][2];
#pragma unroll
        for (int j = 0; j < 8; j++) {
            float v[4];
#pragma unroll
            for (int q = 0; q < 4; q++) { const float h = agg[j][q]; v[q] = fmaf(h, tanh_ap(h), h); }
            o[j][0] = pack_bf16(v[0], v[1]); o[j][1] = pack_bf16(v[2], v[3]);
        }
#pragma unroll
        for (int jp = 0; jp < 4; jp++) {
            const int c = 4 * jp + mi;
            stsm4t(ring0 + rr * 256 + ((c & 8) << 4) + (((c & 7) ^ rr) << 4), o[2 * jp][0], o[2 * jp][1], o[2 * jp + 1][0], o[2 * jp + 1][1]);
        }
        __syncwarp();
#pragma unroll
        for (int i = 0; i < 3; i++) {
            const int idx = lane + 32 * i, row = idx >> 4, c = idx & 15;
            const int nd = b * NPC + (int)lds8(sb + SM_TNODE + w * 8 + (row & 7));
            if (row < nslot && nd < NN) {
                const uint4 v = lds128(ring0 + row * 256 + ((c & 8) << 4) + (((c & 7) ^ row) << 4));
                *(uint4*)((char*)p.out + (size_t)nd * 256 + c * 16) = v;
            }
        }
    }
}

__device__ __align__(16) bf16 g_fb_xa[NN * 128];
__device__ __align__(16) float g_fb_h[NN * 128];

__global__ void fb_node_kernel(const bf16* x, const bf16* uw, const bf16* vw, const bf16* gw, bf16* table) {
    __shared__ float xs[128];
    const int n = blockIdx.x, f = threadIdx.x;
    xs[f] = __bfloat162float(x[n * 128 + f]);
    __syncthreads();
    float a = 0.f, bb = 0.f, v = 0.f, u = 0.f;
    for (int k = 0; k < 128; k++) {
        const float xv = xs[k];
        a += xv * __bfloat162float(gw[k * 128 + f]);
        bb += xv * __bfloat162float(gw[(128 + k) * 128 + f]);
        v += xv * __bfloat162float(vw[k * 128 + f]);
        u += xv * __bfloat162float(uw[k * 128 + f]);
    }
    table[n * 256 + f] = __float2bfloat16(0.5f * bb);
    table[n * 256 + 128 + f] = __float2bfloat16(0.25f * v);
    g_fb_xa[n * 128 + f] = __float2bfloat16(0.5f * a);
    g_fb_h[n * 128 + f] = 0.5f * u;
}
__global__ void fb_edge_kernel(const bf16* e_attr, const int* src, const int* dst, const bf16* gw, const bf16* table) {
    const int e = blockIdx.x, f = threadIdx.x, s = src[e], d = dst[e];
    float z = 0.f;
    for (int k = 0; k < 16; k++) z += __bfloat162float(e_attr[e * 16 + k]) * __bfloat162float(gw[(256 + k) * 128 + f]);
    z = 0.5f * z + __bfloat162float(g_fb_xa[d * 128 + f]) + __bfloat162float(table[s * 256 + f]);
    const float hv = __bfloat162float(table[s * 256 + 128 + f]);
    atomicAdd(&g_fb_h[d * 128 + f], fmaf(hv, tanhf(z), hv));
}
__global__ void fb_out_kernel(bf16* out) {
    const int i = blockIdx.x * 128 + threadIdx.x;
    const float h = g_fb_h[i];
    out[i] = __float2bfloat16(fmaf(h, tanhf(h), h));
}

typedef CUresult (*EncodeFn)(CUtensorMap*, CUtensorMapDataType, cuuint32_t, void*, const cuuint64_t*, const cuuint64_t*,
                             const cuuint32_t*, const cuuint32_t*, CUtensorMapInterleave, CUtensorMapSwizzle,
                             CUtensorMapL2promotion, CUtensorMapFloatOOBfill);

static void make_map(EncodeFn enc, CUtensorMap* tm, const void* base, int rows, int cols, int box_rows) {
    cuuint64_t dims[2] = {(cuuint64_t)cols, (cuuint64_t)rows};
    cuuint64_t strides[1] = {(cuuint64_t)cols * 2};
    cuuint32_t box[2] = {64, (cuuint32_t)box_rows};
    cuuint32_t es[2] = {1, 1};
    enc(tm, CU_TENSOR_MAP_DATA_TYPE_BFLOAT16, 2, (void*)base, dims, strides, box, es, CU_TENSOR_MAP_INTERLEAVE_NONE,
        CU_TENSOR_MAP_SWIZZLE_128B, CU_TENSOR_MAP_L2_PROMOTION_NONE, CU_TENSOR_MAP_FLOAT_OOB_FILL_NONE);
}

}

extern "C" void kernel_launch(void* const* d_in, const int* in_sizes, int n_in, void* d_out, int out_size) {
    using namespace egc;
    (void)in_sizes; (void)n_in; (void)out_size;
    static EncodeFn enc = nullptr;
    static void* table = nullptr;
    static void* xch = nullptr;
    static void* bar = nullptr;
    static bool persistent = false;
    if (!enc) {
        void* fn = nullptr;
        cudaDriverEntryPointQueryResult qr;
        cudaGetDriverEntryPoint("cuTensorMapEncodeTiled", &fn, cudaEnableDefault, &qr);
        enc = (EncodeFn)fn;
        cudaGetSymbolAddress(&table, g_table);
        cudaGetSymbolAddress(&xch, g_xch);
        cudaGetSymbolAddress(&bar, g_bar);
        cudaFuncSetAttribute(egc_kernel, cudaFuncAttributeMaxDynamicSharedMemorySize, SMEM_BYTES);
        int dev = 0, sms = 0, per_sm = 0;
        cudaGetDevice(&dev);
        cudaDeviceGetAttribute(&sms, cudaDevAttrMultiProcessorCount, dev);
        cudaOccupancyMaxActiveBlocksPerMultiprocessor(&per_sm, egc_kernel, NTHR, SMEM_BYTES);
        persistent = enc != nullptr && sms * per_sm >= NCTA;
    }
    if (!persistent) {
        const bf16* x = (const bf16*)d_in[0];
        fb_node_kernel<<<NN, 128, 0, cudaStreamPerThread>>>(x, (const bf16*)d_in[4], (const bf16*)d_in[5], (const bf16*)d_in[6], (bf16*)table);
        fb_edge_kernel<<<EE, 128, 0, cudaStreamPerThread>>>((const bf16*)d_in[1], (const int*)d_in[2], (const int*)d_in[3], (const bf16*)d_in[6], (const bf16*)table);
        fb_out_kernel<<<NN, 128, 0, cudaStreamPerThread>>>((bf16*)d_out);
        return;
    }
    CUtensorMap tm_x, tm_g, tm_u, tm_v, tm_t;
    make_map(enc, &tm_x, d_in[0], NN, 128, 80);
    make_map(enc, &tm_u, d_in[4], 128, 128, 128);
    make_map(enc, &tm_v, d_in[5], 128, 128, 128);
    make_map(enc, &tm_g, d_in[6], 272, 128, 128);
    make_map(enc, &tm_t, table, NN, 256, NPC);
    Params p;
    p.e_attr = (const bf16*)d_in[1];
    p.src = (const int*)d_in[2];
    p.dst = (const int*)d_in[3];
    p.gw = (const bf16*)d_in[6];
    p.out = (bf16*)d_out;
    p.bar = (unsigned*)bar;
    p.xch = (uint4*)xch;
    p.table = (const char*)table;
    egc_kernel<<<NCTA, NTHR, SMEM_BYTES, cudaStreamPerThread>>>(p, tm_x, tm_g, tm_u, tm_v, tm_t);
}
```

```cpp
#include <cuda_runtime.h>
#include <cuda_bf16.h>
#include <cuda.h>
#include <stdint.h>

namespace egc {

typedef __nv_bfloat16 bf16;

constexpr int NN = 10000, EE = 160000;
constexpr int NCTA = 132, NPC = 76, ECH = 1216, NTHR = 512;
constexpr int PIECES = 10, XCAP = 3 * PIECES;
constexpr int TCAP = 96;
constexpr int NSEG = (EE + TCAP - 1) / TCAP;
constexpr int SPIN_LIMIT = 1 << 20;
constexpr uint32_t START_DELAY = 420;

constexpr int STAGE = 4352;
constexpr int SM_R0 = 0;
constexpr int SM_R1 = 16 * STAGE;
constexpr int SM_S = SM_R1;
constexpr int SM_WU = SM_R1 + 8 * STAGE;
constexpr int SM_WA = SM_R1 + 16 * STAGE;
constexpr int SM_X = SM_WA + 32768;
constexpr int SM_C = SM_X + 20480;
constexpr int SM_LSE = SM_C + 4096;
constexpr int SM_LID = SM_LSE + 6144;
constexpr int SM_HIST = SM_LID + 1536;
constexpr int SM_KEYS = SM_HIST + 544;
constexpr int SM_DBIN = SM_KEYS + 512;
constexpr int SM_TDEG = SM_DBIN + 256;
constexpr int SM_TNODE = SM_TDEG + 512;
constexpr int SM_TCNT = SM_TNODE + 128;
constexpr int SM_FLAG = SM_TCNT + 64;
constexpr int NCAP = 63;
constexpr int SM_NL = SM_FLAG + 16;
constexpr int SM_BAR = SM_NL + NPC * NCAP * 4 + 128;
constexpr int SM_END = SM_BAR + 9 * 8;
constexpr int SMEM_BYTES = SM_END + 1024;
static_assert(SM_R1 % 1024 == 0 && SM_WU % 1024 == 0 && SM_WA % 1024 == 0 && SM_X % 1024 == 0 && SM_BAR % 8 == 0 && SM_TDEG % 16 == 0 &&
              SM_LSE % 16 == 0 && SM_LID % 8 == 0 && SM_DBIN % 8 == 0 && SM_TNODE % 8 == 0 && SMEM_BYTES <= 232448, "shared memory map");

__device__ __align__(1024) uint4 g_table[NN * 32];
__device__ __align__(1024) uint4 g_xch[NCTA * NCTA * PIECES];
__device__ __align__(128) unsigned g_bar[32];

__device__ __forceinline__ void mma16816(float* d, uint32_t a0, uint32_t a1, uint32_t a2, uint32_t a3, uint32_t b0, uint32_t b1) {
    asm("mma.sync.aligned.m16n8k16.row.col.f32.bf16.bf16.f32 {%0,%1,%2,%3}, {%4,%5,%6,%7}, {%8,%9}, {%0,%1,%2,%3};"
        : "+f"(d[0]), "+f"(d[1]), "+f"(d[2]), "+f"(d[3]) : "r"(a0), "r"(a1), "r"(a2), "r"(a3), "r"(b0), "r"(b1));
}
__device__ __forceinline__ void mma16816_z(float* d, uint32_t a0, uint32_t a1, uint32_t a2, uint32_t a3, uint32_t b0, uint32_t b1) {
    asm("mma.sync.aligned.m16n8k16.row.col.f32.bf16.bf16.f32 {%0,%1,%2,%3}, {%4,%5,%6,%7}, {%8,%9}, {%10,%10,%10,%10};"
        : "=f"(d[0]), "=f"(d[1]), "=f"(d[2]), "=f"(d[3]) : "r"(a0), "r"(a1), "r"(a2), "r"(a3), "r"(b0), "r"(b1), "f"(0.f));
}
__device__ __forceinline__ void mma1688(float* d, uint32_t a0, uint32_t a1, uint32_t b0) {
    asm("mma.sync.aligned.m16n8k8.row.col.f32.bf16.bf16.f32 {%0,%1,%2,%3}, {%4,%5}, {%6}, {%0,%1,%2,%3};"
        : "+f"(d[0]), "+f"(d[1]), "+f"(d[2]), "+f"(d[3]) : "r"(a0), "r"(a1), "r"(b0));
}
__device__ __forceinline__ void mma1688_z(float* d, uint32_t a0, uint32_t a1, uint32_t b0) {
    asm("mma.sync.aligned.m16n8k8.row.col.f32.bf16.bf16.f32 {%0,%1,%2,%3}, {%4,%5}, {%6}, {%7,%7,%7,%7};"
        : "=f"(d[0]), "=f"(d[1]), "=f"(d[2]), "=f"(d[3]) : "r"(a0), "r"(a1), "r"(b0), "f"(0.f));
}
__device__ __forceinline__ void ldsm4(uint32_t* r, uint32_t addr) {
    asm volatile("ldmatrix.sync.aligned.m8n8.x4.shared.b16 {%0,%1,%2,%3}, [%4];" : "=r"(r[0]), "=r"(r[1]), "=r"(r[2]), "=r"(r[3]) : "r"(addr) : "memory");
}
__device__ __forceinline__ void ldsm4t(uint32_t* r, uint32_t addr) {
    asm volatile("ldmatrix.sync.aligned.m8n8.x4.trans.shared.b16 {%0,%1,%2,%3}, [%4];" : "=r"(r[0]), "=r"(r[1]), "=r"(r[2]), "=r"(r[3]) : "r"(addr) : "memory");
}
__device__ __forceinline__ void ldsm2(uint32_t* r, uint32_t addr) {
    asm volatile("ldmatrix.sync.aligned.m8n8.x2.shared.b16 {%0,%1}, [%2];" : "=r"(r[0]), "=r"(r[1]) : "r"(addr) : "memory");
}
__device__ __forceinline__ void stsm4t(uint32_t addr, uint32_t r0, uint32_t r1, uint32_t r2, uint32_t r3) {
    asm volatile("stmatrix.sync.aligned.m8n8.x4.trans.shared.b16 [%0], {%1,%2,%3,%4};" :: "r"(addr), "r"(r0), "r"(r1), "r"(r2), "r"(r3) : "memory");
}
__device__ __forceinline__ float tanh_ap(float x) { float r; asm("tanh.approx.f32 %0, %1;" : "=f"(r) : "f"(x)); return r; }
__device__ __forceinline__ uint32_t pack_bf16(float lo, float hi) { uint32_t r; asm("cvt.rn.bf16x2.f32 %0, %1, %2;" : "=r"(r) : "f"(hi), "f"(lo)); return r; }
__device__ __forceinline__ uint32_t fma_bf16x2(uint32_t a, uint32_t b, uint32_t c) { uint32_t r; asm("fma.rn.bf16x2 %0, %1, %2, %3;" : "=r"(r) : "r"(a), "r"(b), "r"(c)); return r; }
__device__ __forceinline__ uint32_t mul_bf16x2(uint32_t a, uint32_t b) { uint32_t r; asm("mul.rn.bf16x2 %0, %1, %2;" : "=r"(r) : "r"(a), "r"(b)); return r; }
__device__ __forceinline__ uint32_t seteq_bf16x2(uint32_t a, uint32_t b) { uint32_t r; asm("set.eq.bf16x2.bf16x2 %0, %1, %2;" : "=r"(r) : "r"(a), "r"(b)); return r; }
__device__ __forceinline__ uint32_t prmt(uint32_t a, uint32_t b, uint32_t s) { uint32_t r; asm("prmt.b32 %0, %1, %2, %3;" : "=r"(r) : "r"(a), "r"(b), "r"(s)); return r; }
__device__ __forceinline__ void cp16(uint32_t dst, const void* src) { asm volatile("cp.async.cg.shared.global [%0], [%1], 16;" :: "r"(dst), "l"(src) : "memory"); }
__device__ __forceinline__ void cp16z(uint32_t dst, const void* src, uint32_t sz) { asm volatile("cp.async.cg.shared.global [%0], [%1], 16, %2;" :: "r"(dst), "l"(src), "r"(sz) : "memory"); }
__device__ __forceinline__ const void* madw(uint32_t a, uint32_t m, const void* base) {
    const void* r; asm("mad.wide.u32 %0, %1, %2, %3;" : "=l"(r) : "r"(a), "r"(m), "l"(base)); return r;
}
__device__ __forceinline__ void cp_commit() { asm volatile("cp.async.commit_group;" ::: "memory"); }
template <int N> __device__ __forceinline__ void cp_wait() { asm volatile("cp.async.wait_group %0;" :: "n"(N) : "memory"); }
__device__ __forceinline__ uint4 lds128(uint32_t a) { uint4 v; asm volatile("ld.shared.v4.u32 {%0,%1,%2,%3}, [%4];" : "=r"(v.x), "=r"(v.y), "=r"(v.z), "=r"(v.w) : "r"(a) : "memory"); return v; }
__device__ __forceinline__ uint2 lds64(uint32_t a) { uint2 v; asm volatile("ld.shared.v2.u32 {%0,%1}, [%2];" : "=r"(v.x), "=r"(v.y) : "r"(a) : "memory"); return v; }
__device__ __forceinline__ uint32_t lds32(uint32_t a) { uint32_t v; asm volatile("ld.shared.u32 %0, [%1];" : "=r"(v) : "r"(a) : "memory"); return v; }
__device__ __forceinline__ uint32_t lds8(uint32_t a) { uint32_t v; asm volatile("ld.shared.u8 %0, [%1];" : "=r"(v) : "r"(a) : "memory"); return v; }
__device__ __forceinline__ void sts32(uint32_t a, uint32_t v) { asm volatile("st.shared.u32 [%0], %1;" :: "r"(a), "r"(v) : "memory"); }
__device__ __forceinline__ void sts8(uint32_t a, uint32_t v) { asm volatile("st.shared.u8 [%0], %1;" :: "r"(a), "r"(v) : "memory"); }
__device__ __forceinline__ uint32_t atoms_add(uint32_t a, uint32_t v) { uint32_t r; asm volatile("atom.shared.add.u32 %0, [%1], %2;" : "=r"(r) : "r"(a), "r"(v) : "memory"); return r; }
__device__ __forceinline__ uint32_t atoms_add_p(bool p, uint32_t a, uint32_t v) {
    uint32_t r = 0;
    asm volatile("{\n.reg .pred p;\nsetp.ne.u32 p, %3, 0;\n@p atom.shared.add.u32 %0, [%1], %2;\n}" : "+r"(r) : "r"(a), "r"(v), "r"((uint32_t)p) : "memory");
    return r;
}
__device__ __forceinline__ void st_piece(uint4* p, uint4 v) {
    asm volatile("{\n.reg .b128 q;\n.reg .b64 lo, hi;\nmov.b64 lo, {%1,%2};\nmov.b64 hi, {%3,%4};\nmov.b128 q, {lo, hi};\nst.relaxed.gpu.global.b128 [%0], q;\n}"
                 :: "l"(p), "r"(v.x), "r"(v.y), "r"(v.z), "r"(v.w) : "memory");
}
__device__ __forceinline__ uint4 ld_piece(const uint4* p) {
    uint4 v;
    asm volatile("{\n.reg .b128 q;\n.reg .b64 lo, hi;\nld.relaxed.gpu.global.b128 q, [%4];\nmov.b128 {lo, hi}, q;\nmov.b64 {%0,%1}, lo;\nmov.b64 {%2,%3}, hi;\n}"
                 : "=r"(v.x), "=r"(v.y), "=r"(v.z), "=r"(v.w) : "l"(p) : "memory");
    return v;
}
__device__ __forceinline__ void mbar_init(uint32_t bar, uint32_t cnt) { asm volatile("mbarrier.init.shared::cta.b64 [%0], %1;" :: "r"(bar), "r"(cnt) : "memory"); }
__device__ __forceinline__ void mbar_expect(uint32_t bar, uint32_t bytes) { asm volatile("mbarrier.arrive.expect_tx.shared::cta.b64 _, [%0], %1;" :: "r"(bar), "r"(bytes) : "memory"); }
__device__ __forceinline__ void mbar_wait(uint32_t bar, uint32_t parity) {
    uint32_t ok; int it = 0;
    do {
        asm volatile("{\n.reg .pred p;\nmbarrier.try_wait.parity.shared::cta.b64 p, [%1], %2;\nselp.u32 %0, 1, 0, p;\n}" : "=r"(ok) : "r"(bar), "r"(parity) : "memory");
    } while (!ok && ++it < (1 << 22));
}
__device__ __forceinline__ void tma_load2d(uint32_t dst, const CUtensorMap* tm, int c0, int c1, uint32_t bar) {
    asm volatile("cp.async.bulk.tensor.2d.shared::cluster.global.mbarrier::complete_tx::bytes [%0], [%1, {%3, %4}], [%2];"
                 :: "r"(dst), "l"(tm), "r"(bar), "r"(c0), "r"(c1) : "memory");
}
__device__ __forceinline__ void tma_store2d(const CUtensorMap* tm, int c0, int c1, uint32_t src) {
    asm volatile("cp.async.bulk.tensor.2d.global.shared::cta.bulk_group [%0, {%2, %3}], [%1];"
                 :: "l"(tm), "r"(src), "r"(c0), "r"(c1) : "memory");
}
__device__ __forceinline__ void spin(uint32_t cycles) {
    uint32_t c0, c1;
    asm volatile("mov.u32 %0, %%clock;" : "=r"(c0));
    do { asm volatile("mov.u32 %0, %%clock;" : "=r"(c1)); } while (c1 - c0 < cycles);
}
__device__ __forceinline__ void lt_bar() { asm volatile("bar.sync 3, 256;" ::: "memory"); }
__device__ __forceinline__ void wg_bar(int id) { asm volatile("bar.sync %0, 128;" :: "r"(id) : "memory"); }

__device__ __forceinline__ void wgmma_n80(float (&d)[40], uint64_t da, uint64_t db, int acc) {
    asm volatile("{\n.reg .pred p;\nsetp.ne.b32 p, %42, 0;\n"
        "wgmma.mma_async.sync.aligned.m64n80k16.f32.bf16.bf16 "
        "{%0,%1,%2,%3,%4,%5,%6,%7,%8,%9,%10,%11,%12,%13,%14,%15,%16,%17,%18,%19,"
        "%20,%21,%22,%23,%24,%25,%26,%27,%28,%29,%30,%31,%32,%33,%34,%35,%36,%37,%38,%39}, "
        "%40, %41, p, 1, 1, 1, 0;\n}\n"
        : "+f"(d[0]), "+f"(d[1]), "+f"(d[2]), "+f"(d[3]), "+f"(d[4]), "+f"(d[5]), "+f"(d[6]), "+f"(d[7]), "+f"(d[8]), "+f"(d[9]),
          "+f"(d[10]), "+f"(d[11]), "+f"(d[12]), "+f"(d[13]), "+f"(d[14]), "+f"(d[15]), "+f"(d[16]), "+f"(d[17]), "+f"(d[18]), "+f"(d[19]),
          "+f"(d[20]), "+f"(d[21]), "+f"(d[22]), "+f"(d[23]), "+f"(d[24]), "+f"(d[25]), "+f"(d[26]), "+f"(d[27]), "+f"(d[28]), "+f"(d[29]),
          "+f"(d[30]), "+f"(d[31]), "+f"(d[32]), "+f"(d[33]), "+f"(d[34]), "+f"(d[35]), "+f"(d[36]), "+f"(d[37]), "+f"(d[38]), "+f"(d[39])
        : "l"(da), "l"(db), "r"(acc));
}

__device__ __forceinline__ void gemm_issue(float (&d)[40], uint32_t wbase, uint32_t xbase) {
    asm volatile("wgmma.fence.sync.aligned;" ::: "memory");
#pragma unroll
    for (int s = 0; s < 8; s++) {
        const uint32_t aa = wbase + s * 2048, ab = xbase + (s >> 2) * 10240 + (s & 3) * 32;
        const uint64_t da = (uint64_t)((aa & 0x3FFFF) >> 4) | ((uint64_t)64 << 16) | ((uint64_t)64 << 32) | ((uint64_t)1 << 62);
        const uint64_t db = (uint64_t)((ab & 0x3FFFF) >> 4) | ((uint64_t)1 << 16) | ((uint64_t)64 << 32) | ((uint64_t)1 << 62);
        wgmma_n80(d, da, db, s > 0);
    }
    asm volatile("wgmma.commit_group.sync.aligned;" ::: "memory");
}
__device__ __forceinline__ void gemm_wait(float (&d)[40]) {
    asm volatile("wgmma.wait_group.sync.aligned 0;" ::: "memory");
#pragma unroll
    for (int i = 0; i < 40; i++) asm volatile("" : "+f"(d[i]) :: "memory");
}
__device__ __forceinline__ void gemm_store(const float (&d)[40], float sc, uint32_t base, int w4, int lane) {
    const int mi = lane >> 3, rr = lane & 7;
    const uint32_t sa = base + (rr + 8 * (mi >> 1)) * 128 + (((2 * w4 + (mi & 1)) ^ rr) << 4);
#pragma unroll
    for (int p = 0; p < 5; p++) {
        const float* q = d + 8 * p;
        stsm4t(sa + p * 2048, pack_bf16(q[0] * sc, q[1] * sc), pack_bf16(q[2] * sc, q[3] * sc),
               pack_bf16(q[4] * sc, q[5] * sc), pack_bf16(q[6] * sc, q[7] * sc));
    }
}

struct Params {
    const int* dst;
    const int* src;
    unsigned* bar;
    uint4* xch;
    const bf16* gw;
    const bf16* e_attr;
    const char* table;
    bf16* out;
};

__global__ void __launch_bounds__(NTHR, 1)
egc_kernel(const Params p, const __grid_constant__ CUtensorMap tm_x, const __grid_constant__ CUtensorMap tm_g,
           const __grid_constant__ CUtensorMap tm_u, const __grid_constant__ CUtensorMap tm_v, const __grid_constant__ CUtensorMap tm_t) {
    extern __shared__ unsigned char smem_raw[];
    const uint32_t sb = ((uint32_t)__cvta_generic_to_shared(smem_raw) + 1023u) & ~1023u;
    const int tid = threadIdx.x, lane = tid & 31, b = blockIdx.x;
    const int w = __shfl_sync(0xffffffffu, tid >> 5, 0);
    const int wq = w >> 2, w4 = w & 3;
    const int g = lane >> 2, t = lane & 3, mi = lane >> 3, rr = lane & 7;

    uint32_t Cf[8][4];
    auto load_cf = [&]() {
        const int krow = rr + 8 * (mi >> 1);
#pragma unroll
        for (int j = 0; j < 8; j++) {
            const int c = 2 * j + (mi & 1);
            ldsm4t(Cf[j], sb + SM_C + krow * 256 + ((c & 8) << 4) + (((c & 7) ^ rr) << 4));
#pragma unroll
            for (int q = 0; q < 4; q++) Cf[j][q] = mul_bf16x2(Cf[j][q], 0x3F003F00u);
        }
    };
    uint32_t xAf[8][2];
    float agg[8][4];
    const uint32_t ident = (g == 2 * t) ? 0x3F80u : ((g == 2 * t + 1) ? 0x3F800000u : 0u);
    const int nslot = (w < 12) ? 5 : 4;
    auto load_node_frags = [&]() {
        const int mynode = lds8(sb + SM_TNODE + w * 8 + ((rr < nslot) ? rr : 0));
#pragma unroll
        for (int jp = 0; jp < 4; jp++) {
            const int c = 4 * jp + mi;
            const uint32_t off = mynode * 128 + (((c & 7) ^ (mynode & 7)) << 4);
            uint32_t q[4];
            ldsm4t(q, sb + SM_WA + (c >> 3) * 16384 + off);
            xAf[2 * jp][0] = q[0]; xAf[2 * jp][1] = q[1]; xAf[2 * jp + 1][0] = q[2]; xAf[2 * jp + 1][1] = q[3];
            ldsm4t(q, sb + SM_X + (c >> 3) * 10240 + off);
            mma1688_z(agg[2 * jp], q[0], q[1], ident);
            mma1688_z(agg[2 * jp + 1], q[2], q[3], ident);
        }
    };
    uint32_t bar_target = 0;
    constexpr int LT = 256;
    if (wq < 2) {
        uint32_t epoch = 0;
        {
            const int r = tid >> 4, c = tid & 15;
            cp16(sb + SM_C + r * 256 + ((c & 8) << 4) + (((c & 7) ^ (r & 7)) << 4), p.gw + (256 + r) * 128 + c * 8);
            cp_commit();
        }
        if (tid == 0) {
            asm volatile("ld.relaxed.gpu.global.u32 %0, [%1];" : "=r"(epoch) : "l"(p.bar) : "memory");
            for (int i = 0; i < 9; i++) mbar_init(sb + SM_BAR + i * 8, 1);
            asm volatile("fence.mbarrier_init.release.cluster;" ::: "memory");
            const uint32_t bx = sb + SM_BAR;
            mbar_expect(bx, 20480);
#pragma unroll
            for (int i = 0; i < 8; i++) mbar_expect(bx + 8 + i * 8, 16384);
            spin(START_DELAY);
            tma_load2d(sb + SM_X, &tm_x, 0, b * NPC, bx);
            tma_load2d(sb + SM_X + 10240, &tm_x, 64, b * NPC, bx);
            tma_load2d(sb + SM_R0, &tm_g, 0, 128, bx + 8);
            tma_load2d(sb + SM_R0 + 16384, &tm_g, 64, 128, bx + 16);
            tma_load2d(sb + SM_R0 + 2 * 16384, &tm_v, 0, 0, bx + 24);
            tma_load2d(sb + SM_R0 + 3 * 16384, &tm_v, 64, 0, bx + 32);
        }
        cp_wait<0>();
        asm volatile("bar.sync 6, 256;" ::: "memory");
        asm volatile("bar.arrive 8, 512;" ::: "memory");
        load_cf();
        float d[40];
        const uint32_t xt = sb + SM_X;
        const bool elect = (w4 == 0 && lane == 0);
        mbar_wait(sb + SM_BAR, 0);
#pragma unroll 1
        for (int r = 0; r < 4; r++) {
            const uint32_t wt = sb + ((r < 2) ? SM_R0 + r * 32768 : ((r == 2) ? SM_WA : SM_WU)) + wq * 16384;
            mbar_wait(sb + SM_BAR + 8 + (2 * r + wq) * 8, 0);
            gemm_issue(d, wt, xt);
            if (r == 0 && tid == 0) {
#pragma unroll
                for (int i = 0; i < 2; i++) {
                    tma_load2d(sb + SM_WA + i * 16384, &tm_g, i * 64, 0, sb + SM_BAR + 8 + (4 + i) * 8);
                    tma_load2d(sb + SM_WU + i * 16384, &tm_u, i * 64, 0, sb + SM_BAR + 8 + (6 + i) * 8);
                }
            }
            if (r == 2) {
                asm volatile("bar.sync 4, 512;" ::: "memory");
                if (elect) {
                    asm volatile("cp.async.bulk.wait_group 0;" ::: "memory");
                    asm volatile("fence.proxy.async.global;" ::: "memory");
                    asm volatile("red.relaxed.gpu.global.add.u32 [%0], 1;" :: "l"(p.bar) : "memory");
                }
            }
            if (r == 3 && tid == 0) {
                const int e0 = b * ECH, ne = min(ECH, EE - e0);
                asm volatile("cp.async.bulk.prefetch.L2.global [%0], %1;" :: "l"(p.e_attr + (size_t)e0 * 16), "r"(ne * 32) : "memory");
            }
            __syncwarp();
            gemm_wait(d);
            if (r < 3) wg_bar(1 + wq); else asm volatile("bar.sync 6, 256;" ::: "memory");
            gemm_store(d, (r == 1) ? 0.25f : 0.5f, (r < 3) ? wt : xt + wq * 10240, w4, lane);
            if (r < 2) {
                asm volatile("fence.proxy.async.shared::cta;" ::: "memory");
                wg_bar(1 + wq);
                if (elect) {
                    tma_store2d(&tm_t, (2 * r + wq) * 64, b * NPC, wt);
                    asm volatile("cp.async.bulk.commit_group;" ::: "memory");
                }
                __syncwarp();
            }
        }

        bar_target = (epoch / (2 * NCTA) + 1) * (2 * NCTA);
    } else {
        const int lt = tid - LT;
        int ed[5], es[5];
        uint32_t epoch = 0;
        {
            const int e4 = b * ECH + 4 * lt, e1 = b * ECH + 1024 + lt;
            const bool ok4 = e4 < EE, ok1 = (lt < ECH - 1024) && (e1 < EE);
            const int4 d4 = ok4 ? __ldg((const int4*)(p.dst + e4)) : make_int4(-1, -1, -1, -1);
            ed[4] = ok1 ? __ldg(p.dst + e1) : -1;
            const int4 s4 = ok4 ? __ldg((const int4*)(p.src + e4)) : make_int4(0, 0, 0, 0);
            es[4] = ok1 ? __ldg(p.src + e1) : 0;
            ed[0] = d4.x; ed[1] = d4.y; ed[2] = d4.z; ed[3] = d4.w;
            es[0] = s4.x; es[1] = s4.y; es[2] = s4.z; es[3] = s4.w;
        }
        if (lt == 0) asm volatile("ld.relaxed.gpu.global.u32 %0, [%1];" : "=r"(epoch) : "l"(p.bar) : "memory");
        if (lt < 136) sts32(sb + SM_HIST + lt * 4, 0);
        if (lt < 128) { sts32(sb + SM_KEYS + lt * 4, 0); sts32(sb + SM_TDEG + lt * 4, 0); }
        if (lt < 64) sts32(sb + SM_DBIN + lt * 4, 0);
        if (lt == 0) sts32(sb + SM_FLAG, 0);
        lt_bar();
        {
            uint32_t jj[5], rk[5];
#pragma unroll
            for (int m = 0; m < 5; m++) {
                jj[m] = (ed[m] >= 0) ? (((uint32_t)ed[m] * 55189u) >> 22) : (132 + (lane & 3));
                rk[m] = atoms_add(sb + SM_HIST + jj[m] * 4, 1);
            }
#pragma unroll
            for (int m = 0; m < 5; m++) {
                const uint32_t loc = (uint32_t)ed[m] - jj[m] * NPC;
                const uint32_t q = (rk[m] * 43691u) >> 17;
                const uint32_t off = jj[m] * (PIECES * 16) + q * 16 + (rk[m] - 3 * q + 1) * 4;
                sts32(sb + SM_S + ((ed[m] >= 0 && rk[m] < XCAP) ? off : NCTA * PIECES * 16 + lane * 4),
                      (uint32_t)es[m] | (loc << 14) | ((uint32_t)((m < 4) ? 4 * lt + m : 1024 + lt) << 21));
            }
        }
        if (lt == 0) sts32(sb + SM_FLAG + 4, epoch / (2 * NCTA));
        lt_bar();
        const uint32_t bar_q = lds32(sb + SM_FLAG + 4);
        epoch = (bar_q + 1) & 0xFFFFFF;
        {
            uint4 v[6]; uint32_t c[6];
#pragma unroll
            for (int m = 0; m < 6; m++) {
                const int pc = min(lt + m * LT, NCTA * PIECES - 1);
                v[m] = lds128(sb + SM_S + pc * 16);
                c[m] = lds32(sb + SM_HIST + ((pc * 6554) >> 16) * 4);
            }
#pragma unroll
            for (int m = 0; m < 6; m++) {
                const int pc = lt + m * LT;
                const int j = (pc * 6554) >> 16, q = pc - j * PIECES;
                if ((m < 5 || pc < NCTA * PIECES) && (q < 4 || c[m] > 3 * (q & ~1) || b >= 128)) {
                    v[m].x = (epoch << 8) | min(c[m], 255u);
                    st_piece(p.xch + (((j * (PIECES / 2) + (q >> 1)) * NCTA + b) * 2 + (q & 1)), v[m]);
                }
            }
        }
        asm volatile("bar.arrive 4, 512;" ::: "memory");
        lt_bar();
        if (lt == 0) asm volatile("red.relaxed.gpu.global.add.u32 [%0], 1;" :: "l"(p.bar + 1) : "memory");
        asm volatile("bar.sync 8, 512;" ::: "memory");
        load_cf();
        if (lt == 0) {
            uint32_t v; int it = 0;
            const uint32_t target = bar_q * NCTA + NCTA * 17 / 20;
            do { asm volatile("ld.relaxed.gpu.global.u32 %0, [%1];" : "=r"(v) : "l"(p.bar + 1) : "memory"); }
            while ((int)(v - target) < 0 && ++it < SPIN_LIMIT);
        }
        lt_bar();
        uint4 pv[6];
        const int pi5 = 128 + ((lt >> 1) & 3), pq5 = 2 * (lt >> 3) + (lt & 1);
        const uint4* px0 = p.xch + b * (NCTA * PIECES) + lt;
        const uint4* px5 = p.xch + b * (NCTA * PIECES) + (lt >> 3) * (2 * NCTA) + 256 + (lt & 7);
        const uint32_t tg = epoch << 8;
        auto fetch = [&](const uint4* a) {
            uint4 v = ld_piece(a);
            int it = 0;
            while (((v.x ^ tg) >> 8) && ++it < SPIN_LIMIT) { __nanosleep(100); v = ld_piece(a); }
            return v;
        };
        pv[0] = ld_piece(px0);
        pv[1] = ld_piece(px0 + 2 * NCTA);
        pv[5] = (lt < 4 * PIECES) ? ld_piece(px5) : make_uint4(tg, 0, 0, 0);
        for (int it = 0; (((pv[0].x ^ tg) | (pv[1].x ^ tg) | (pv[5].x ^ tg)) >> 8) && it < SPIN_LIMIT; it++) {
            __nanosleep(100);
            if ((pv[0].x ^ tg) >> 8) pv[0] = ld_piece(px0);
            if ((pv[1].x ^ tg) >> 8) pv[1] = ld_piece(px0 + 2 * NCTA);
            if ((pv[5].x ^ tg) >> 8) pv[5] = ld_piece(px5);
        }
        const int cnt = pv[0].x & 255, cnt5 = pv[5].x & 255;
#pragma unroll
        for (int m = 2; m < 5; m++) pv[m] = (cnt > 6 * m) ? ld_piece(px0 + m * (2 * NCTA)) : make_uint4(tg, 0, 0, 0);
        if (cnt > XCAP || cnt5 > XCAP) sts32(sb + SM_FLAG, 1);
        const uint32_t dmy = (96 + lane) * 4;
        uint32_t ao[9], rk[9];
        auto count = [&](int m, int o) {
            const int nv = (m < 5) ? cnt - 3 * (2 * m + (lt & 1)) : cnt5 - 3 * pq5;
#pragma unroll
            for (int s = 0; s < 3; s++) {
                const uint32_t pl = (s == 0) ? pv[m].y : ((s == 1) ? pv[m].z : pv[m].w);
                ao[o + s] = (nv > s) ? ((pl >> 12) & 0x1FC) : dmy;
                rk[o + s] = atoms_add(sb + SM_KEYS + ao[o + s], 1);
            }
        };
        auto put = [&](int m, int o) {
            const uint32_t e0s = (uint32_t)(((m < 5) ? (lt >> 1) : pi5) * ECH) << 14;
#pragma unroll
            for (int s = 0; s < 3; s++) {
                const uint32_t pl = (s == 0) ? pv[m].y : ((s == 1) ? pv[m].z : pv[m].w);
                const bool ok = ao[o + s] < 96 * 4 && rk[o + s] < NCAP;
                sts32(sb + SM_NL + (ok ? ao[o + s] * NCAP + rk[o + s] * 4 : NPC * NCAP * 4 + lane * 4), (pl & 0x3FFF) + ((pl >> 21) << 14) + e0s);
            }
        };
        count(0, 0);
        count(1, 3);
        const bool has5 = lt < 64;
        if (has5) count(5, 6);
        put(0, 0);
        put(1, 3);
        if (has5) put(5, 6);
        if (((pv[2].x ^ tg) | (pv[3].x ^ tg) | (pv[4].x ^ tg)) >> 8) {
#pragma unroll
            for (int m = 2; m < 5; m++) if (cnt > 6 * m) pv[m] = fetch(px0 + m * (2 * NCTA));
        }
#pragma unroll
        for (int m = 2; m < 5; m++) {
            if (__any_sync(0xffffffffu, cnt > 6 * m)) { count(m, 0); put(m, 0); }
        }
        lt_bar();
        if (lt < 96) {
            const uint32_t deg = (lt < NPC) ? lds32(sb + SM_KEYS + lt * 4) : 0;
            const uint32_t bin = 63 - min(deg, 63u);
            const uint32_t r0 = atoms_add_p(lt < NPC, sb + SM_DBIN + bin * 4, 1);
            if (deg > NCAP) sts32(sb + SM_FLAG, 1);
            asm volatile("bar.sync 5, 96;" ::: "memory");
            const uint2 c2 = lds64(sb + SM_DBIN + lane * 8);
            uint32_t inc = c2.x + c2.y;
#pragma unroll
            for (int o = 1; o < 32; o <<= 1) { const uint32_t u = __shfl_up_sync(0xffffffffu, inc, o); if (lane >= o) inc += u; }
            const uint32_t ex = inc - c2.x - c2.y;
            const uint32_t pe = __shfl_sync(0xffffffffu, ex, bin >> 1), p0 = __shfl_sync(0xffffffffu, c2.x, bin >> 1);
            const int rank = pe + ((bin & 1) ? p0 : 0) + r0;
            const int k = rank >> 4, pos = rank & 15;
            const int tile = (k == 4) ? 11 - pos : ((pos < 4) ? 12 + ((k & 1) ? 3 - pos : pos) : ((k < 3) ? pos - 4 : 15 - pos));
            if (lt < NPC) {
                sts32(sb + SM_TDEG + (tile * 8 + k) * 4, deg);
                sts8(sb + SM_TNODE + tile * 8 + k, lt);
            }
        }
    }
    __syncthreads();
    bool slow = lds32(sb + SM_FLAG) != 0;

    constexpr uint32_t RD = SM_R1 - SM_R0;
    const uint32_t ring0 = sb + SM_R0 + w * STAGE;
    const char* tab_l = p.table + lane * 16;
    asm volatile("" : "+l"(tab_l));
    const char* e_l = (const char*)p.e_attr + (mi & 1) * 16;
    asm volatile("" : "+l"(e_l));
    const uint32_t cpo = lane * 16;
    const uint32_t elo = 4096 + rr * 32 + (((mi & 1) ^ ((rr >> 2) & 1)) << 4);
    const uint32_t lsrc = sb + SM_LSE + w * TCAP * 4, lid = sb + SM_LID + w * TCAP;
    const uint32_t lec = rr * 4;

    auto issue_full = [&](uint32_t lp, uint32_t dl) {
        const uint4 s0 = lds128(lp), s1 = lds128(lp + 16);
        const uint32_t eo = lds32(lp + lec);
        const uint32_t sv[8] = {s0.x, s0.y, s0.z, s0.w, s1.x, s1.y, s1.z, s1.w};
#pragma unroll
        for (int j = 0; j < 8; j++) cp16(ring0 + dl + (cpo ^ (j << 4)) + j * 512, madw(sv[j] & 0x3FFF, 512, tab_l));
        cp16(ring0 + dl + elo, madw(eo >> 14, 32, e_l));
    };
    auto issue0 = [&]() {
        const int cnt = lds32(sb + SM_TCNT + w * 4), nit = (cnt + 7) >> 3;
        if (nit > 0) {
            const int pad = nit * 8 - cnt;
            const uint4 s0 = lds128(lsrc), s1 = lds128(lsrc + 16);
            const uint32_t eo = lds32(lsrc + lec);
            const uint32_t sv[8] = {s0.x, s0.y, s0.z, s0.w, s1.x, s1.y, s1.z, s1.w};
#pragma unroll
            for (int j = 0; j < 8; j++) cp16z(ring0 + (cpo ^ (j << 4)) + j * 512, madw(sv[j] & 0x3FFF, 512, tab_l), (j >= pad) ? 16 : 0);
            cp16z(ring0 + elo, madw(eo >> 14, 32, e_l), (rr >= pad) ? 16 : 0);
        }
        cp_commit();
    };
    auto issue1 = [&]() {
        if ((int)lds32(sb + SM_TCNT + w * 4) > 8) issue_full(lsrc + 32, RD);
        cp_commit();
    };
    uint32_t bar_v = 0;
    bool over = false;
    if (tid == 0) asm volatile("ld.relaxed.gpu.global.u32 %0, [%1];" : "=r"(bar_v) : "l"(p.bar) : "memory");
    if (!slow) {
        const uint2 tn = lds64(sb + SM_TNODE + w * 8);
        const uint4 dg = lds128(sb + SM_TDEG + w * 32);
        const uint32_t p1 = dg.x, p2 = p1 + dg.y, p3 = p2 + dg.z, p4 = p3 + dg.w, tot = p4 + lds32(sb + SM_TDEG + w * 32 + 16);
        const uint32_t pad = (0u - tot) & 7u;
        if (lane == 0) sts32(sb + SM_TCNT + w * 4, tot);
        over = tot + pad > TCAP;
        uint32_t wd[TCAP / 32], sl[TCAP / 32];
#pragma unroll
        for (int r = 0; r < TCAP / 32; r++) {
            const uint32_t q = lane + 32 * r - pad;
            sl[r] = (q >= p1) + (q >= p2) + (q >= p3) + (q >= p4);
            const uint32_t pre = (q >= p4) ? p4 : ((q >= p3) ? p3 : ((q >= p2) ? p2 : ((q >= p1) ? p1 : 0)));
            const uint32_t node = prmt(tn.x, tn.y, sl[r]) & 0xFF;
            wd[r] = lds32(sb + SM_NL + ((q < tot) ? (node * NCAP + q - pre) * 4 : 0));
        }
#pragma unroll
        for (int r = 0; r < TCAP / 32; r++) {
            const uint32_t q = lane + 32 * r - pad;
            sts32(lsrc + (lane + 32 * r) * 4, (q < tot) ? wd[r] : 0);
            sts8(lid + lane + 32 * r, (q < tot) ? sl[r] * 16 : 0x7F);
        }
    }
    if (tid == 0) {
        int it = 0;
        while ((int)(bar_v - bar_target) < 0 && ++it < SPIN_LIMIT)
            asm volatile("ld.relaxed.gpu.global.u32 %0, [%1];" : "=r"(bar_v) : "l"(p.bar) : "memory");
    }
    slow = __syncthreads_or(slow || over);
    if (!slow) {
        issue0();
        issue1();
    } else {
        if (tid < NPC) sts8(sb + SM_TNODE + (tid & 15) * 8 + (tid >> 4), tid);
        __syncthreads();
    }
    load_node_frags();

    const uint32_t ldo = rr * 512 + ((mi ^ rr) << 4);
    const uint32_t sel = (g | ((8 | g) << 4) | (g << 8) | ((8 | g) << 12)) |
                         (((2 * t) | ((8 | (2 * t)) << 4) | ((2 * t + 1) << 8) | ((8 | (2 * t + 1)) << 12)) << 16);
    const uint32_t gg = (g * 16) | ((g * 16) << 16);
    const uint32_t tt = (t * 32) | ((t * 32 + 16) << 16);

    auto compute = [&](uint32_t st, uint32_t idp) {
        uint32_t eb[2];
        ldsm2(eb, st + elo);
        const uint2 iw = lds64(idp);
        const uint32_t sx = seteq_bf16x2(prmt(iw.x, iw.y, sel), tt);
        const uint32_t sa = seteq_bf16x2(prmt(iw.x, iw.y, sel >> 16), gg);
#pragma unroll
        for (int jj = 0; jj < 4; jj++) {
            uint32_t xb[4], hv[4];
            const uint32_t la = st + (ldo ^ ((jj & 1) << 6)) + (jj >> 1) * 128;
            ldsm4(xb, la);
            ldsm4t(hv, la + 256);
#pragma unroll
            for (int u = 0; u < 2; u++) {
                const int j = 2 * jj + u;
                float d[4];
                mma16816_z(d, Cf[j][0], Cf[j][1], Cf[j][2], Cf[j][3], eb[0], eb[1]);
                mma1688(d, xAf[j][0], xAf[j][1], sx);
                mma16816(d, ident, 0u, 0u, ident, xb[2 * u], xb[2 * u + 1]);
                const uint32_t m0 = fma_bf16x2(pack_bf16(tanh_ap(d[0]), tanh_ap(d[1])), hv[2 * u], hv[2 * u]);
                const uint32_t m1 = fma_bf16x2(pack_bf16(tanh_ap(d[2]), tanh_ap(d[3])), hv[2 * u + 1], hv[2 * u + 1]);
                mma1688(agg[j], m0, m1, sa);
            }
        }
    };

    const int nseg = slow ? NSEG : 1;
#pragma unroll 1
    for (int seg = 0; seg < nseg; seg++) {
        if (slow) {
            __syncthreads();
            if (tid < 16) sts32(sb + SM_TCNT + tid * 4, 0);
            __syncthreads();
            const int e = seg * TCAP + tid;
            int loc = -1; uint32_t r = 0;
            if (tid < TCAP && e < EE) {
                const int dd = __ldg(p.dst + e) - b * NPC;
                if (dd >= 0 && dd < NPC) { loc = dd; r = atoms_add(sb + SM_TCNT + (loc & 15) * 4, 1); }
            }
            __syncthreads();
            if (loc >= 0) {
                const uint32_t tile = loc & 15, tot = lds32(sb + SM_TCNT + tile * 4);
                const uint32_t pos = tile * TCAP + ((0u - tot) & 7u) + r;
                sts32(sb + SM_LSE + pos * 4, (uint32_t)__ldg(p.src + e) | ((uint32_t)e << 14));
                sts8(sb + SM_LID + pos, (loc >> 4) << 4);
            }
            const int pad = (0 - (int)lds32(sb + SM_TCNT + w * 4)) & 7;
            if (lane < pad) { sts8(sb + SM_LID + w * TCAP + lane, 0x7F); sts32(sb + SM_LSE + (w * TCAP + lane) * 4, 0); }
            __syncthreads();
            issue0();
            issue1();
        }
        const int nit = __shfl_sync(0xffffffffu, ((int)lds32(sb + SM_TCNT + w * 4) + 7) >> 3, 0);
        uint32_t st = ring0, so = ring0 + RD, idp = lid;
        const uint32_t lend = lsrc + nit * 32;
        constexpr int AVG_NIT = (EE + NCTA * 128 - 1) / (NCTA * 128);
        constexpr int HEAVY = EE / NN * NPC * 207 / 200;
        const int ctot = __reduce_add_sync(0xffffffffu, (lane < 16) ? (int)lds32(sb + SM_TCNT + lane * 4) : 0);
        const bool eager = nit > AVG_NIT || ctot > HEAVY;
        uint32_t lc = lsrc + 32;
        uint32_t li = min(lsrc + 64, lend);
#pragma unroll 1
        for (; lc <= lend; lc += 32, idp += 8) {
            if (li > lc) cp_wait<1>(); else cp_wait<0>();
            __syncwarp();
            if (li == lc && li < lend) { issue_full(li, so - ring0); cp_commit(); li += 32; }
            compute(st, idp);
            if (eager && li == lc + 32 && li < lend) { __syncwarp(); issue_full(li, st - ring0); cp_commit(); li += 32; }
            const uint32_t tmp = st; st = so; so = tmp;
        }
        cp_wait<0>();
        __syncwarp();
    }

    {
        uint32_t o[8][2];
#pragma unroll
        for (int j = 0; j < 8; j++) {
            float v[4];
#pragma unroll
            for (int q = 0; q < 4; q++) { const float h = agg[j][q]; v[q] = fmaf(h, tanh_ap(h), h); }
            o[j][0] = pack_bf16(v[0], v[1]); o[j][1] = pack_bf16(v[2], v[3]);
        }
#pragma unroll
        for (int jp = 0; jp < 4; jp++) {
            const int c = 4 * jp + mi;
            stsm4t(ring0 + rr * 256 + ((c & 8) << 4) + (((c & 7) ^ rr) << 4), o[2 * jp][0], o[2 * jp][1], o[2 * jp + 1][0], o[2 * jp + 1][1]);
        }
        __syncwarp();
#pragma unroll
        for (int i = 0; i < 3; i++) {
            const int idx = lane + 32 * i, row = idx >> 4, c = idx & 15;
            const int nd = b * NPC + (int)lds8(sb + SM_TNODE + w * 8 + (row & 7));
            if (row < nslot && nd < NN) {
                const uint4 v = lds128(ring0 + row * 256 + ((c & 8) << 4) + (((c & 7) ^ row) << 4));
                *(uint4*)((char*)p.out + (size_t)nd * 256 + c * 16) = v;
            }
        }
    }
}

__device__ __align__(16) bf16 g_fb_xa[NN * 128];
__device__ __align__(16) float g_fb_h[NN * 128];

__global__ void fb_node_kernel(const bf16* x, const bf16* uw, const bf16* vw, const bf16* gw, bf16* table) {
    __shared__ float xs[128];
    const int n = blockIdx.x, f = threadIdx.x;
    xs[f] = __bfloat162float(x[n * 128 + f]);
    __syncthreads();
    float a = 0.f, bb = 0.f, v = 0.f, u = 0.f;
    for (int k = 0; k < 128; k++) {
        const float xv = xs[k];
        a += xv * __bfloat162float(gw[k * 128 + f]);
        bb += xv * __bfloat162float(gw[(128 + k) * 128 + f]);
        v += xv * __bfloat162float(vw[k * 128 + f]);
        u += xv * __bfloat162float(uw[k * 128 + f]);
    }
    table[n * 256 + f] = __float2bfloat16(0.5f * bb);
    table[n * 256 + 128 + f] = __float2bfloat16(0.25f * v);
    g_fb_xa[n * 128 + f] = __float2bfloat16(0.5f * a);
    g_fb_h[n * 128 + f] = 0.5f * u;
}
__global__ void fb_edge_kernel(const bf16* e_attr, const int* src, const int* dst, const bf16* gw, const bf16* table) {
    const int e = blockIdx.x, f = threadIdx.x, s = src[e], d = dst[e];
    float z = 0.f;
    for (int k = 0; k < 16; k++) z += __bfloat162float(e_attr[e * 16 + k]) * __bfloat162float(gw[(256 + k) * 128 + f]);
    z = 0.5f * z + __bfloat162float(g_fb_xa[d * 128 + f]) + __bfloat162float(table[s * 256 + f]);
    const float hv = __bfloat162float(table[s * 256 + 128 + f]);
    atomicAdd(&g_fb_h[d * 128 + f], fmaf(hv, tanhf(z), hv));
}
__global__ void fb_out_kernel(bf16* out) {
    const int i = blockIdx.x * 128 + threadIdx.x;
    const float h = g_fb_h[i];
    out[i] = __float2bfloat16(fmaf(h, tanhf(h), h));
}

typedef CUresult (*EncodeFn)(CUtensorMap*, CUtensorMapDataType, cuuint32_t, void*, const cuuint64_t*, const cuuint64_t*,
                             const cuuint32_t*, const cuuint32_t*, CUtensorMapInterleave, CUtensorMapSwizzle,
                             CUtensorMapL2promotion, CUtensorMapFloatOOBfill);

static void make_map(EncodeFn enc, CUtensorMap* tm, const void* base, int rows, int cols, int box_rows) {
    cuuint64_t dims[2] = {(cuuint64_t)cols, (cuuint64_t)rows};
    cuuint64_t strides[1] = {(cuuint64_t)cols * 2};
    cuuint32_t box[2] = {64, (cuuint32_t)box_rows};
    cuuint32_t es[2] = {1, 1};
    enc(tm, CU_TENSOR_MAP_DATA_TYPE_BFLOAT16, 2, (void*)base, dims, strides, box, es, CU_TENSOR_MAP_INTERLEAVE_NONE,
        CU_TENSOR_MAP_SWIZZLE_128B, CU_TENSOR_MAP_L2_PROMOTION_NONE, CU_TENSOR_MAP_FLOAT_OOB_FILL_NONE);
}

}

extern "C" void kernel_launch(void* const* d_in, const int* in_sizes, int n_in, void* d_out, int out_size) {
    using namespace egc;
    (void)in_sizes; (void)n_in; (void)out_size;
    static EncodeFn enc = nullptr;
    static void* table = nullptr;
    static void* xch = nullptr;
    static void* bar = nullptr;
    static bool persistent = false;
    if (!enc) {
        void* fn = nullptr;
        cudaDriverEntryPointQueryResult qr;
        cudaGetDriverEntryPoint("cuTensorMapEncodeTiled", &fn, cudaEnableDefault, &qr);
        enc = (EncodeFn)fn;
        cudaGetSymbolAddress(&table, g_table);
        cudaGetSymbolAddress(&xch, g_xch);
        cudaGetSymbolAddress(&bar, g_bar);
        cudaFuncSetAttribute(egc_kernel, cudaFuncAttributeMaxDynamicSharedMemorySize, SMEM_BYTES);
        int dev = 0, sms = 0, per_sm = 0;
        cudaGetDevice(&dev);
        cudaDeviceGetAttribute(&sms, cudaDevAttrMultiProcessorCount, dev);
        cudaOccupancyMaxActiveBlocksPerMultiprocessor(&per_sm, egc_kernel, NTHR, SMEM_BYTES);
        persistent = enc != nullptr && sms * per_sm >= NCTA;
    }
    if (!persistent) {
        const bf16* x = (const bf16*)d_in[0];
        fb_node_kernel<<<NN, 128, 0, cudaStreamPerThread>>>(x, (const bf16*)d_in[4], (const bf16*)d_in[5], (const bf16*)d_in[6], (bf16*)table);
        fb_edge_kernel<<<EE, 128, 0, cudaStreamPerThread>>>((const bf16*)d_in[1], (const int*)d_in[2], (const int*)d_in[3], (const bf16*)d_in[6], (const bf16*)table);
        fb_out_kernel<<<NN, 128, 0, cudaStreamPerThread>>>((bf16*)d_out);
        return;
    }
    CUtensorMap tm_x, tm_g, tm_u, tm_v, tm_t;
    make_map(enc, &tm_x, d_in[0], NN, 128, 80);
    make_map(enc, &tm_u, d_in[4], 128, 128, 128);
    make_map(enc, &tm_v, d_in[5], 128, 128, 128);
    make_map(enc, &tm_g, d_in[6], 272, 128, 128);
    make_map(enc, &tm_t, table, NN, 256, NPC);
    Params p;
    p.e_attr = (const bf16*)d_in[1];
    p.src = (const int*)d_in[2];
    p.dst = (const int*)d_in[3];
    p.gw = (const bf16*)d_in[6];
    p.out = (bf16*)d_out;
    p.bar = (unsigned*)bar;
    p.xch = (uint4*)xch;
    p.table = (const char*)table;
    egc_kernel<<<NCTA, NTHR, SMEM_BYTES, cudaStreamPerThread>>>(p, tm_x, tm_g, tm_u, tm_v, tm_t);
}
```

```cpp
#include <cuda_runtime.h>
#include <cuda_bf16.h>
#include <cuda.h>
#include <stdint.h>

namespace egc {

typedef __nv_bfloat16 bf16;

constexpr int NN = 10000, EE = 160000;
constexpr int NCTA = 132, NPC = 76, ECH = 1216, NTHR = 512;
constexpr int PIECES = 10, XCAP = 3 * PIECES;
constexpr int TCAP = 96;
constexpr int NSEG = (EE + TCAP - 1) / TCAP;
constexpr int SPIN_LIMIT = 1 << 20;
constexpr uint32_t START_DELAY = 360;

constexpr int STAGE = 4352;
constexpr int SM_R0 = 0;
constexpr int SM_R1 = 16 * STAGE;
constexpr int SM_S = SM_R1;
constexpr int SM_WU = SM_R1 + 8 * STAGE;
constexpr int SM_WA = SM_R1 + 16 * STAGE;
constexpr int SM_X = SM_WA + 32768;
constexpr int SM_C = SM_X + 20480;
constexpr int SM_LSE = SM_C + 4096;
constexpr int SM_LID = SM_LSE + 6144;
constexpr int SM_HIST = SM_LID + 1536;
constexpr int SM_KEYS = SM_HIST + 544;
constexpr int SM_DBIN = SM_KEYS + 512;
constexpr int SM_TDEG = SM_DBIN + 256;
constexpr int SM_TNODE = SM_TDEG + 512;
constexpr int SM_TCNT = SM_TNODE + 128;
constexpr int SM_FLAG = SM_TCNT + 64;
constexpr int NCAP = 63;
constexpr int SM_NL = SM_FLAG + 16;
constexpr int SM_BAR = SM_NL + NPC * NCAP * 4 + 128;
constexpr int SM_END = SM_BAR + 9 * 8;
constexpr int SMEM_BYTES = SM_END + 1024;
static_assert(SM_R1 % 1024 == 0 && SM_WU % 1024 == 0 && SM_WA % 1024 == 0 && SM_X % 1024 == 0 && SM_BAR % 8 == 0 && SM_TDEG % 16 == 0 &&
              SM_LSE % 16 == 0 && SM_LID % 8 == 0 && SM_DBIN % 8 == 0 && SM_TNODE % 8 == 0 && SMEM_BYTES <= 232448, "shared memory map");

__device__ __align__(1024) uint4 g_table[NN * 32];
__device__ __align__(1024) uint4 g_xch[NCTA * NCTA * PIECES];
__device__ __align__(128) unsigned g_bar[32];

__device__ __forceinline__ void mma16816(float* d, uint32_t a0, uint32_t a1, uint32_t a2, uint32_t a3, uint32_t b0, uint32_t b1) {
    asm("mma.sync.aligned.m16n8k16.row.col.f32.bf16.bf16.f32 {%0,%1,%2,%3}, {%4,%5,%6,%7}, {%8,%9}, {%0,%1,%2,%3};"
        : "+f"(d[0]), "+f"(d[1]), "+f"(d[2]), "+f"(d[3]) : "r"(a0), "r"(a1), "r"(a2), "r"(a3), "r"(b0), "r"(b1));
}
__device__ __forceinline__ void mma16816_z(float* d, uint32_t a0, uint32_t a1, uint32_t a2, uint32_t a3, uint32_t b0, uint32_t b1) {
    asm("mma.sync.aligned.m16n8k16.row.col.f32.bf16.bf16.f32 {%0,%1,%2,%3}, {%4,%5,%6,%7}, {%8,%9}, {%10,%10,%10,%10};"
        : "=f"(d[0]), "=f"(d[1]), "=f"(d[2]), "=f"(d[3]) : "r"(a0), "r"(a1), "r"(a2), "r"(a3), "r"(b0), "r"(b1), "f"(0.f));
}
__device__ __forceinline__ void mma1688(float* d, uint32_t a0, uint32_t a1, uint32_t b0) {
    asm("mma.sync.aligned.m16n8k8.row.col.f32.bf16.bf16.f32 {%0,%1,%2,%3}, {%4,%5}, {%6}, {%0,%1,%2,%3};"
        : "+f"(d[0]), "+f"(d[1]), "+f"(d[2]), "+f"(d[3]) : "r"(a0), "r"(a1), "r"(b0));
}
__device__ __forceinline__ void mma1688_z(float* d, uint32_t a0, uint32_t a1, uint32_t b0) {
    asm("mma.sync.aligned.m16n8k8.row.col.f32.bf16.bf16.f32 {%0,%1,%2,%3}, {%4,%5}, {%6}, {%7,%7,%7,%7};"
        : "=f"(d[0]), "=f"(d[1]), "=f"(d[2]), "=f"(d[3]) : "r"(a0), "r"(a1), "r"(b0), "f"(0.f));
}
__device__ __forceinline__ void ldsm4(uint32_t* r, uint32_t addr) {
    asm volatile("ldmatrix.sync.aligned.m8n8.x4.shared.b16 {%0,%1,%2,%3}, [%4];" : "=r"(r[0]), "=r"(r[1]), "=r"(r[2]), "=r"(r[3]) : "r"(addr) : "memory");
}
__device__ __forceinline__ void ldsm4t(uint32_t* r, uint32_t addr) {
    asm volatile("ldmatrix.sync.aligned.m8n8.x4.trans.shared.b16 {%0,%1,%2,%3}, [%4];" : "=r"(r[0]), "=r"(r[1]), "=r"(r[2]), "=r"(r[3]) : "r"(addr) : "memory");
}
__device__ __forceinline__ void ldsm2(uint32_t* r, uint32_t addr) {
    asm volatile("ldmatrix.sync.aligned.m8n8.x2.shared.b16 {%0,%1}, [%2];" : "=r"(r[0]), "=r"(r[1]) : "r"(addr) : "memory");
}
__device__ __forceinline__ void stsm4t(uint32_t addr, uint32_t r0, uint32_t r1, uint32_t r2, uint32_t r3) {
    asm volatile("stmatrix.sync.aligned.m8n8.x4.trans.shared.b16 [%0], {%1,%2,%3,%4};" :: "r"(addr), "r"(r0), "r"(r1), "r"(r2), "r"(r3) : "memory");
}
__device__ __forceinline__ float tanh_ap(float x) { float r; asm("tanh.approx.f32 %0, %1;" : "=f"(r) : "f"(x)); return r; }
__device__ __forceinline__ uint32_t pack_bf16(float lo, float hi) { uint32_t r; asm("cvt.rn.bf16x2.f32 %0, %1, %2;" : "=r"(r) : "f"(hi), "f"(lo)); return r; }
__device__ __forceinline__ uint32_t fma_bf16x2(uint32_t a, uint32_t b, uint32_t c) { uint32_t r; asm("fma.rn.bf16x2 %0, %1, %2, %3;" : "=r"(r) : "r"(a), "r"(b), "r"(c)); return r; }
__device__ __forceinline__ uint32_t mul_bf16x2(uint32_t a, uint32_t b) { uint32_t r; asm("mul.rn.bf16x2 %0, %1, %2;" : "=r"(r) : "r"(a), "r"(b)); return r; }
__device__ __forceinline__ uint32_t seteq_bf16x2(uint32_t a, uint32_t b) { uint32_t r; asm("set.eq.bf16x2.bf16x2 %0, %1, %2;" : "=r"(r) : "r"(a), "r"(b)); return r; }
__device__ __forceinline__ uint32_t prmt(uint32_t a, uint32_t b, uint32_t s) { uint32_t r; asm("prmt.b32 %0, %1, %2, %3;" : "=r"(r) : "r"(a), "r"(b), "r"(s)); return r; }
__device__ __forceinline__ void cp16(uint32_t dst, const void* src) { asm volatile("cp.async.cg.shared.global [%0], [%1], 16;" :: "r"(dst), "l"(src) : "memory"); }
__device__ __forceinline__ void cp16z(uint32_t dst, const void* src, uint32_t sz) { asm volatile("cp.async.cg.shared.global [%0], [%1], 16, %2;" :: "r"(dst), "l"(src), "r"(sz) : "memory"); }
__device__ __forceinline__ const void* madw(uint32_t a, uint32_t m, const void* base) {
    const void* r; asm("mad.wide.u32 %0, %1, %2, %3;" : "=l"(r) : "r"(a), "r"(m), "l"(base)); return r;
}
__device__ __forceinline__ void cp_commit() { asm volatile("cp.async.commit_group;" ::: "memory"); }
template <int N> __device__ __forceinline__ void cp_wait() { asm volatile("cp.async.wait_group %0;" :: "n"(N) : "memory"); }
__device__ __forceinline__ uint4 lds128(uint32_t a) { uint4 v; asm volatile("ld.shared.v4.u32 {%0,%1,%2,%3}, [%4];" : "=r"(v.x), "=r"(v.y), "=r"(v.z), "=r"(v.w) : "r"(a) : "memory"); return v; }
__device__ __forceinline__ uint2 lds64(uint32_t a) { uint2 v; asm volatile("ld.shared.v2.u32 {%0,%1}, [%2];" : "=r"(v.x), "=r"(v.y) : "r"(a) : "memory"); return v; }
__device__ __forceinline__ uint32_t lds32(uint32_t a) { uint32_t v; asm volatile("ld.shared.u32 %0, [%1];" : "=r"(v) : "r"(a) : "memory"); return v; }
__device__ __forceinline__ uint32_t lds8(uint32_t a) { uint32_t v; asm volatile("ld.shared.u8 %0, [%1];" : "=r"(v) : "r"(a) : "memory"); return v; }
__device__ __forceinline__ void sts32(uint32_t a, uint32_t v) { asm volatile("st.shared.u32 [%0], %1;" :: "r"(a), "r"(v) : "memory"); }
__device__ __forceinline__ void sts8(uint32_t a, uint32_t v) { asm volatile("st.shared.u8 [%0], %1;" :: "r"(a), "r"(v) : "memory"); }
__device__ __forceinline__ uint32_t atoms_add(uint32_t a, uint32_t v) { uint32_t r; asm volatile("atom.shared.add.u32 %0, [%1], %2;" : "=r"(r) : "r"(a), "r"(v) : "memory"); return r; }
__device__ __forceinline__ uint32_t atoms_add_p(bool p, uint32_t a, uint32_t v) {
    uint32_t r = 0;
    asm volatile("{\n.reg .pred p;\nsetp.ne.u32 p, %3, 0;\n@p atom.shared.add.u32 %0, [%1], %2;\n}" : "+r"(r) : "r"(a), "r"(v), "r"((uint32_t)p) : "memory");
    return r;
}
__device__ __forceinline__ void st_piece(uint4* p, uint4 v) {
    asm volatile("{\n.reg .b128 q;\n.reg .b64 lo, hi;\nmov.b64 lo, {%1,%2};\nmov.b64 hi, {%3,%4};\nmov.b128 q, {lo, hi};\nst.relaxed.gpu.global.b128 [%0], q;\n}"
                 :: "l"(p), "r"(v.x), "r"(v.y), "r"(v.z), "r"(v.w) : "memory");
}
__device__ __forceinline__ uint4 ld_piece(const uint4* p) {
    uint4 v;
    asm volatile("{\n.reg .b128 q;\n.reg .b64 lo, hi;\nld.relaxed.gpu.global.b128 q, [%4];\nmov.b128 {lo, hi}, q;\nmov.b64 {%0,%1}, lo;\nmov.b64 {%2,%3}, hi;\n}"
                 : "=r"(v.x), "=r"(v.y), "=r"(v.z), "=r"(v.w) : "l"(p) : "memory");
    return v;
}
__device__ __forceinline__ void mbar_init(uint32_t bar, uint32_t cnt) { asm volatile("mbarrier.init.shared::cta.b64 [%0], %1;" :: "r"(bar), "r"(cnt) : "memory"); }
__device__ __forceinline__ void mbar_expect(uint32_t bar, uint32_t bytes) { asm volatile("mbarrier.arrive.expect_tx.shared::cta.b64 _, [%0], %1;" :: "r"(bar), "r"(bytes) : "memory"); }
__device__ __forceinline__ void mbar_wait(uint32_t bar, uint32_t parity) {
    uint32_t ok; int it = 0;
    do {
        asm volatile("{\n.reg .pred p;\nmbarrier.try_wait.parity.shared::cta.b64 p, [%1], %2;\nselp.u32 %0, 1, 0, p;\n}" : "=r"(ok) : "r"(bar), "r"(parity) : "memory");
    } while (!ok && ++it < (1 << 22));
}
__device__ __forceinline__ void tma_load2d(uint32_t dst, const CUtensorMap* tm, int c0, int c1, uint32_t bar) {
    asm volatile("cp.async.bulk.tensor.2d.shared::cluster.global.mbarrier::complete_tx::bytes [%0], [%1, {%3, %4}], [%2];"
                 :: "r"(dst), "l"(tm), "r"(bar), "r"(c0), "r"(c1) : "memory");
}
__device__ __forceinline__ void tma_store2d(const CUtensorMap* tm, int c0, int c1, uint32_t src) {
    asm volatile("cp.async.bulk.tensor.2d.global.shared::cta.bulk_group [%0, {%2, %3}], [%1];"
                 :: "l"(tm), "r"(src), "r"(c0), "r"(c1) : "memory");
}
__device__ __forceinline__ void spin(uint32_t cycles) {
    uint32_t c0, c1;
    asm volatile("mov.u32 %0, %%clock;" : "=r"(c0));
    do { asm volatile("mov.u32 %0, %%clock;" : "=r"(c1)); } while (c1 - c0 < cycles);
}
__device__ __forceinline__ void lt_bar() { asm volatile("bar.sync 3, 256;" ::: "memory"); }
__device__ __forceinline__ void wg_bar(int id) { asm volatile("bar.sync %0, 128;" :: "r"(id) : "memory"); }

__device__ __forceinline__ void wgmma_n80(float (&d)[40], uint64_t da, uint64_t db, int acc) {
    asm volatile("{\n.reg .pred p;\nsetp.ne.b32 p, %42, 0;\n"
        "wgmma.mma_async.sync.aligned.m64n80k16.f32.bf16.bf16 "
        "{%0,%1,%2,%3,%4,%5,%6,%7,%8,%9,%10,%11,%12,%13,%14,%15,%16,%17,%18,%19,"
        "%20,%21,%22,%23,%24,%25,%26,%27,%28,%29,%30,%31,%32,%33,%34,%35,%36,%37,%38,%39}, "
        "%40, %41, p, 1, 1, 1, 0;\n}\n"
        : "+f"(d[0]), "+f"(d[1]), "+f"(d[2]), "+f"(d[3]), "+f"(d[4]), "+f"(d[5]), "+f"(d[6]), "+f"(d[7]), "+f"(d[8]), "+f"(d[9]),
          "+f"(d[10]), "+f"(d[11]), "+f"(d[12]), "+f"(d[13]), "+f"(d[14]), "+f"(d[15]), "+f"(d[16]), "+f"(d[17]), "+f"(d[18]), "+f"(d[19]),
          "+f"(d[20]), "+f"(d[21]), "+f"(d[22]), "+f"(d[23]), "+f"(d[24]), "+f"(d[25]), "+f"(d[26]), "+f"(d[27]), "+f"(d[28]), "+f"(d[29]),
          "+f"(d[30]), "+f"(d[31]), "+f"(d[32]), "+f"(d[33]), "+f"(d[34]), "+f"(d[35]), "+f"(d[36]), "+f"(d[37]), "+f"(d[38]), "+f"(d[39])
        : "l"(da), "l"(db), "r"(acc));
}

__device__ __forceinline__ void gemm_issue(float (&d)[40], uint32_t wbase, uint32_t xbase) {
    asm volatile("wgmma.fence.sync.aligned;" ::: "memory");
#pragma unroll
    for (int s = 0; s < 8; s++) {
        const uint32_t aa = wbase + s * 2048, ab = xbase + (s >> 2) * 10240 + (s & 3) * 32;
        const uint64_t da = (uint64_t)((aa & 0x3FFFF) >> 4) | ((uint64_t)64 << 16) | ((uint64_t)64 << 32) | ((uint64_t)1 << 62);
        const uint64_t db = (uint64_t)((ab & 0x3FFFF) >> 4) | ((uint64_t)1 << 16) | ((uint64_t)64 << 32) | ((uint64_t)1 << 62);
        wgmma_n80(d, da, db, s > 0);
    }
    asm volatile("wgmma.commit_group.sync.aligned;" ::: "memory");
}
__device__ __forceinline__ void gemm_wait(float (&d)[40]) {
    asm volatile("wgmma.wait_group.sync.aligned 0;" ::: "memory");
#pragma unroll
    for (int i = 0; i < 40; i++) asm volatile("" : "+f"(d[i]) :: "memory");
}
__device__ __forceinline__ void gemm_store(const float (&d)[40], float sc, uint32_t base, int w4, int lane) {
    const int mi = lane >> 3, rr = lane & 7;
    const uint32_t sa = base + (rr + 8 * (mi >> 1)) * 128 + (((2 * w4 + (mi & 1)) ^ rr) << 4);
#pragma unroll
    for (int p = 0; p < 5; p++) {
        const float* q = d + 8 * p;
        stsm4t(sa + p * 2048, pack_bf16(q[0] * sc, q[1] * sc), pack_bf16(q[2] * sc, q[3] * sc),
               pack_bf16(q[4] * sc, q[5] * sc), pack_bf16(q[6] * sc, q[7] * sc));
    }
}

struct Params {
    const int* dst;
    const int* src;
    unsigned* bar;
    uint4* xch;
    const bf16* gw;
    const bf16* e_attr;
    const char* table;
    bf16* out;
};

__global__ void __launch_bounds__(NTHR, 1)
egc_kernel(const Params p, const __grid_constant__ CUtensorMap tm_x, const __grid_constant__ CUtensorMap tm_g,
           const __grid_constant__ CUtensorMap tm_u, const __grid_constant__ CUtensorMap tm_v, const __grid_constant__ CUtensorMap tm_t) {
    extern __shared__ unsigned char smem_raw[];
    const uint32_t sb = ((uint32_t)__cvta_generic_to_shared(smem_raw) + 1023u) & ~1023u;
    const int tid = threadIdx.x, lane = tid & 31, b = blockIdx.x;
    const int w = __shfl_sync(0xffffffffu, tid >> 5, 0);
    const int wq = w >> 2, w4 = w & 3;
    const int g = lane >> 2, t = lane & 3, mi = lane >> 3, rr = lane & 7;

    uint32_t Cf[8][4];
    auto load_cf = [&]() {
        const int krow = rr + 8 * (mi >> 1);
#pragma unroll
        for (int j = 0; j < 8; j++) {
            const int c = 2 * j + (mi & 1);
            ldsm4t(Cf[j], sb + SM_C + krow * 256 + ((c & 8) << 4) + (((c & 7) ^ rr) << 4));
#pragma unroll
            for (int q = 0; q < 4; q++) Cf[j][q] = mul_bf16x2(Cf[j][q], 0x3F003F00u);
        }
    };
    uint32_t xAf[8][2];
    float agg[8][4];
    const uint32_t ident = (g == 2 * t) ? 0x3F80u : ((g == 2 * t + 1) ? 0x3F800000u : 0u);
    const int nslot = (w < 12) ? 5 : 4;
    auto load_node_frags = [&]() {
        const int mynode = lds8(sb + SM_TNODE + w * 8 + ((rr < nslot) ? rr : 0));
#pragma unroll
        for (int jp = 0; jp < 4; jp++) {
            const int c = 4 * jp + mi;
            const uint32_t off = mynode * 128 + (((c & 7) ^ (mynode & 7)) << 4);
            uint32_t q[4];
            ldsm4t(q, sb + SM_WA + (c >> 3) * 16384 + off);
            xAf[2 * jp][0] = q[0]; xAf[2 * jp][1] = q[1]; xAf[2 * jp + 1][0] = q[2]; xAf[2 * jp + 1][1] = q[3];
            ldsm4t(q, sb + SM_X + (c >> 3) * 10240 + off);
            mma1688_z(agg[2 * jp], q[0], q[1], ident);
            mma1688_z(agg[2 * jp + 1], q[2], q[3], ident);
        }
    };
    uint32_t bar_target = 0;
    constexpr int LT = 256;
    if (wq < 2) {
        uint32_t epoch = 0;
        {
            const int r = tid >> 4, c = tid & 15;
            cp16(sb + SM_C + r * 256 + ((c & 8) << 4) + (((c & 7) ^ (r & 7)) << 4), p.gw + (256 + r) * 128 + c * 8);
            cp_commit();
        }
        if (tid == 0) {
            asm volatile("ld.relaxed.gpu.global.u32 %0, [%1];" : "=r"(epoch) : "l"(p.bar) : "memory");
            for (int i = 0; i < 9; i++) mbar_init(sb + SM_BAR + i * 8, 1);
            asm volatile("fence.mbarrier_init.release.cluster;" ::: "memory");
            const uint32_t bx = sb + SM_BAR;
            mbar_expect(bx, 20480);
#pragma unroll
            for (int i = 0; i < 8; i++) mbar_expect(bx + 8 + i * 8, 16384);
            spin(START_DELAY);
            tma_load2d(sb + SM_X, &tm_x, 0, b * NPC, bx);
            tma_load2d(sb + SM_X + 10240, &tm_x, 64, b * NPC, bx);
            tma_load2d(sb + SM_R0, &tm_g, 0, 128, bx + 8);
            tma_load2d(sb + SM_R0 + 16384, &tm_g, 64, 128, bx + 16);
            tma_load2d(sb + SM_R0 + 2 * 16384, &tm_v, 0, 0, bx + 24);
            tma_load2d(sb + SM_R0 + 3 * 16384, &tm_v, 64, 0, bx + 32);
        }
        cp_wait<0>();
        asm volatile("bar.sync 6, 256;" ::: "memory");
        asm volatile("bar.arrive 8, 512;" ::: "memory");
        load_cf();
        float d[40];
        const uint32_t xt = sb + SM_X;
        const bool elect = (w4 == 0 && lane == 0);
        mbar_wait(sb + SM_BAR, 0);
#pragma unroll 1
        for (int r = 0; r < 4; r++) {
            const uint32_t wt = sb + ((r < 2) ? SM_R0 + r * 32768 : ((r == 2) ? SM_WA : SM_WU)) + wq * 16384;
            mbar_wait(sb + SM_BAR + 8 + (2 * r + wq) * 8, 0);
            if (r == 0 && wq == 1) asm volatile("bar.sync 10, 256;" ::: "memory");
            gemm_issue(d, wt, xt);
            if (r == 0 && tid == 0) {
#pragma unroll
                for (int i = 0; i < 2; i++) {
                    tma_load2d(sb + SM_WA + i * 16384, &tm_g, i * 64, 0, sb + SM_BAR + 8 + (4 + i) * 8);
                    tma_load2d(sb + SM_WU + i * 16384, &tm_u, i * 64, 0, sb + SM_BAR + 8 + (6 + i) * 8);
                }
            }
            if (r == 2) {
                asm volatile("bar.sync 4, 512;" ::: "memory");
                if (elect) {
                    asm volatile("cp.async.bulk.wait_group 0;" ::: "memory");
                    asm volatile("fence.proxy.async.global;" ::: "memory");
                    asm volatile("red.relaxed.gpu.global.add.u32 [%0], 1;" :: "l"(p.bar) : "memory");
                }
            }
            if (r == 3 && tid == 0) {
                const int e0 = b * ECH, ne = min(ECH, EE - e0);
                asm volatile("cp.async.bulk.prefetch.L2.global [%0], %1;" :: "l"(p.e_attr + (size_t)e0 * 16), "r"(ne * 32) : "memory");
            }
            __syncwarp();
            gemm_wait(d);
            if (r == 0 && wq == 0) asm volatile("bar.arrive 10, 256;" ::: "memory");
            if (r < 3) wg_bar(1 + wq); else asm volatile("bar.sync 6, 256;" ::: "memory");
            gemm_store(d, (r == 1) ? 0.25f : 0.5f, (r < 3) ? wt : xt + wq * 10240, w4, lane);
            if (r < 2) {
                asm volatile("fence.proxy.async.shared::cta;" ::: "memory");
                wg_bar(1 + wq);
                if (elect) {
                    tma_store2d(&tm_t, (2 * r + wq) * 64, b * NPC, wt);
                    asm volatile("cp.async.bulk.commit_group;" ::: "memory");
                }
                __syncwarp();
            }
        }

        bar_target = (epoch / (2 * NCTA) + 1) * (2 * NCTA);
    } else {
        const int lt = tid - LT;
        int ed[5], es[5];
        uint32_t epoch = 0;
        {
            const int e4 = b * ECH + 4 * lt, e1 = b * ECH + 1024 + lt;
            const bool ok4 = e4 < EE, ok1 = (lt < ECH - 1024) && (e1 < EE);
            const int4 d4 = ok4 ? __ldg((const int4*)(p.dst + e4)) : make_int4(-1, -1, -1, -1);
            ed[4] = ok1 ? __ldg(p.dst + e1) : -1;
            const int4 s4 = ok4 ? __ldg((const int4*)(p.src + e4)) : make_int4(0, 0, 0, 0);
            es[4] = ok1 ? __ldg(p.src + e1) : 0;
            ed[0] = d4.x; ed[1] = d4.y; ed[2] = d4.z; ed[3] = d4.w;
            es[0] = s4.x; es[1] = s4.y; es[2] = s4.z; es[3] = s4.w;
        }
        if (lt == 0) asm volatile("ld.relaxed.gpu.global.u32 %0, [%1];" : "=r"(epoch) : "l"(p.bar) : "memory");
        if (lt < 136) sts32(sb + SM_HIST + lt * 4, 0);
        if (lt < 128) { sts32(sb + SM_KEYS + lt * 4, 0); sts32(sb + SM_TDEG + lt * 4, 0); }
        if (lt < 64) sts32(sb + SM_DBIN + lt * 4, 0);
        if (lt == 0) sts32(sb + SM_FLAG, 0);
        lt_bar();
        {
            uint32_t jj[5], rk[5];
#pragma unroll
            for (int m = 0; m < 5; m++) {
                jj[m] = (ed[m] >= 0) ? (((uint32_t)ed[m] * 55189u) >> 22) : (132 + (lane & 3));
                rk[m] = atoms_add(sb + SM_HIST + jj[m] * 4, 1);
            }
#pragma unroll
            for (int m = 0; m < 5; m++) {
                const uint32_t loc = (uint32_t)ed[m] - jj[m] * NPC;
                const uint32_t q = (rk[m] * 43691u) >> 17;
                const uint32_t off = jj[m] * (PIECES * 16) + q * 16 + (rk[m] - 3 * q + 1) * 4;
                sts32(sb + SM_S + ((ed[m] >= 0 && rk[m] < XCAP) ? off : NCTA * PIECES * 16 + lane * 4),
                      (uint32_t)es[m] | (loc << 14) | ((uint32_t)((m < 4) ? 4 * lt + m : 1024 + lt) << 21));
            }
        }
        if (lt == 0) sts32(sb + SM_FLAG + 4, epoch / (2 * NCTA));
        lt_bar();
        const uint32_t bar_q = lds32(sb + SM_FLAG + 4);
        epoch = (bar_q + 1) & 0xFFFFFF;
        {
            uint4 v[6]; uint32_t c[6];
#pragma unroll
            for (int m = 0; m < 6; m++) {
                const int pc = min(lt + m * LT, NCTA * PIECES - 1);
                v[m] = lds128(sb + SM_S + pc * 16);
                c[m] = lds32(sb + SM_HIST + ((pc * 6554) >> 16) * 4);
            }
#pragma unroll
            for (int m = 0; m < 6; m++) {
                const int pc = lt + m * LT;
                const int j = (pc * 6554) >> 16, q = pc - j * PIECES;
                if ((m < 5 || pc < NCTA * PIECES) && (q < 4 || c[m] > 3 * (q & ~1))) {
                    v[m].x = (epoch << 8) | min(c[m], 255u);
                    st_piece(p.xch + ((q < 4) ? (j * NCTA + b) * 4 + q : NCTA * NCTA * 4 + (j * NCTA + b) * 6 + q - 4), v[m]);
                }
            }
        }
        asm volatile("bar.arrive 4, 512;" ::: "memory");
        lt_bar();
        if (lt == 0) asm volatile("red.relaxed.gpu.global.add.u32 [%0], 1;" :: "l"(p.bar + 1) : "memory");
        asm volatile("bar.sync 8, 512;" ::: "memory");
        load_cf();
        if (lt == 0) {
            uint32_t v; int it = 0;
            const uint32_t target = bar_q * NCTA + NCTA * 9 / 10;
            do { asm volatile("ld.relaxed.gpu.global.u32 %0, [%1];" : "=r"(v) : "l"(p.bar + 1) : "memory"); }
            while ((int)(v - target) < 0 && ++it < SPIN_LIMIT);
        }
        lt_bar();
        const int r4 = lt & 3;
        const uint4* pm = p.xch + b * (NCTA * 4) + lt;
        const uint4* po = p.xch + NCTA * NCTA * 4 + (b * NCTA + (lt >> 2)) * 6 + r4;
        const uint32_t tg = epoch << 8;
        auto fetch = [&](const uint4* a) {
            uint4 v = ld_piece(a);
            int it = 0;
            while (((v.x ^ tg) >> 8) && ++it < SPIN_LIMIT) { __nanosleep(100); v = ld_piece(a); }
            return v;
        };
        uint4 pv[3], pw[3];
        pv[0] = ld_piece(pm);
        pv[1] = ld_piece(pm + LT);
        pv[2] = (lt < 16) ? ld_piece(pm + 2 * LT) : make_uint4(tg, 0, 0, 0);
        for (int it = 0; (((pv[0].x ^ tg) | (pv[1].x ^ tg) | (pv[2].x ^ tg)) >> 8) && it < SPIN_LIMIT; it++) {
            __nanosleep(100);
#pragma unroll
            for (int m = 0; m < 3; m++) if ((pv[m].x ^ tg) >> 8) pv[m] = ld_piece(pm + m * LT);
        }
        int cn[3];
        const int thr = 12 + 3 * (r4 & 2);
#pragma unroll
        for (int m = 0; m < 3; m++) {
            cn[m] = pv[m].x & 255;
            pw[m] = (cn[m] > thr) ? ld_piece(po + m * (64 * 6)) : make_uint4(tg, 0, 0, 0);
        }
        if (cn[0] > XCAP || cn[1] > XCAP || cn[2] > XCAP) sts32(sb + SM_FLAG, 1);
        const uint32_t dmy = (96 + lane) * 4;
        uint32_t ao[9], rk[9];
        auto count = [&](const uint4& v, int nv, int o) {
#pragma unroll
            for (int s = 0; s < 3; s++) {
                const uint32_t pl = (s == 0) ? v.y : ((s == 1) ? v.z : v.w);
                ao[o + s] = (nv > s) ? ((pl >> 12) & 0x1FC) : dmy;
                rk[o + s] = atoms_add(sb + SM_KEYS + ao[o + s], 1);
            }
        };
        auto put = [&](const uint4& v, int m, int o) {
            const uint32_t e0s = (uint32_t)((64 * m + (lt >> 2)) * ECH) << 14;
#pragma unroll
            for (int s = 0; s < 3; s++) {
                const uint32_t pl = (s == 0) ? v.y : ((s == 1) ? v.z : v.w);
                const bool ok = ao[o + s] < 96 * 4 && rk[o + s] < NCAP;
                sts32(sb + SM_NL + (ok ? ao[o + s] * NCAP + rk[o + s] * 4 : NPC * NCAP * 4 + lane * 4), (pl & 0x3FFF) + ((pl >> 21) << 14) + e0s);
            }
        };
        const bool has2 = lt < 32;
        count(pv[0], cn[0] - 3 * r4, 0);
        count(pv[1], cn[1] - 3 * r4, 3);
        if (has2) count(pv[2], cn[2] - 3 * r4, 6);
        put(pv[0], 0, 0);
        put(pv[1], 1, 3);
        if (has2) put(pv[2], 2, 6);
        if (((pw[0].x ^ tg) | (pw[1].x ^ tg) | (pw[2].x ^ tg)) >> 8) {
#pragma unroll
            for (int m = 0; m < 3; m++) if (cn[m] > thr) pw[m] = fetch(po + m * (64 * 6));
        }
#pragma unroll
        for (int m = 0; m < 3; m++) {
            if (__any_sync(0xffffffffu, cn[m] > thr)) { count(pw[m], (cn[m] > thr) ? cn[m] - 3 * (4 + r4) : 0, 0); put(pw[m], m, 0); }
        }
#pragma unroll 1
        for (int m = 0; m < 3; m++) {
            const int c = (m == 0) ? cn[0] : ((m == 1) ? cn[1] : cn[2]);
            if (__any_sync(0xffffffffu, c > 24)) {
                const bool use = c > 24 && r4 < 2;
                const uint4 v = use ? fetch(po + m * (64 * 6) + 4) : make_uint4(tg, 0, 0, 0);
                count(v, use ? c - 3 * (8 + r4) : 0, 0);
                put(v, m, 0);
            }
        }
        lt_bar();
        if (lt < 96) {
            const uint32_t deg = (lt < NPC) ? lds32(sb + SM_KEYS + lt * 4) : 0;
            const uint32_t bin = 63 - min(deg, 63u);
            const uint32_t r0 = atoms_add_p(lt < NPC, sb + SM_DBIN + bin * 4, 1);
            if (deg > NCAP) sts32(sb + SM_FLAG, 1);
            asm volatile("bar.sync 5, 96;" ::: "memory");
            const uint2 c2 = lds64(sb + SM_DBIN + lane * 8);
            uint32_t inc = c2.x + c2.y;
#pragma unroll
            for (int o = 1; o < 32; o <<= 1) { const uint32_t u = __shfl_up_sync(0xffffffffu, inc, o); if (lane >= o) inc += u; }
            const uint32_t ex = inc - c2.x - c2.y;
            const uint32_t pe = __shfl_sync(0xffffffffu, ex, bin >> 1), p0 = __shfl_sync(0xffffffffu, c2.x, bin >> 1);
            const int rank = pe + ((bin & 1) ? p0 : 0) + r0;
            const int k = rank >> 4, pos = rank & 15;
            const int tile = (k == 4) ? 11 - pos : ((pos < 4) ? 12 + ((k & 1) ? 3 - pos : pos) : ((k < 3) ? pos - 4 : 15 - pos));
            if (lt < NPC) {
                sts32(sb + SM_TDEG + (tile * 8 + k) * 4, deg);
                sts8(sb + SM_TNODE + tile * 8 + k, lt);
            }
        }
    }
    __syncthreads();
    bool slow = lds32(sb + SM_FLAG) != 0;

    constexpr uint32_t RD = SM_R1 - SM_R0;
    const uint32_t ring0 = sb + SM_R0 + w * STAGE;
    const char* tab_l = p.table + lane * 16;
    asm volatile("" : "+l"(tab_l));
    const char* e_l = (const char*)p.e_attr + (mi & 1) * 16;
    asm volatile("" : "+l"(e_l));
    const uint32_t cpo = lane * 16;
    const uint32_t elo = 4096 + rr * 32 + (((mi & 1) ^ ((rr >> 2) & 1)) << 4);
    const uint32_t lsrc = sb + SM_LSE + w * TCAP * 4, lid = sb + SM_LID + w * TCAP;
    const uint32_t lec = rr * 4;

    auto issue_full = [&](uint32_t lp, uint32_t dl) {
        const uint4 s0 = lds128(lp), s1 = lds128(lp + 16);
        const uint32_t eo = lds32(lp + lec);
        const uint32_t sv[8] = {s0.x, s0.y, s0.z, s0.w, s1.x, s1.y, s1.z, s1.w};
#pragma unroll
        for (int j = 0; j < 8; j++) cp16(ring0 + dl + (cpo ^ (j << 4)) + j * 512, madw(sv[j] & 0x3FFF, 512, tab_l));
        cp16(ring0 + dl + elo, madw(eo >> 14, 32, e_l));
    };
    auto issue0 = [&]() {
        const int cnt = lds32(sb + SM_TCNT + w * 4), nit = (cnt + 7) >> 3;
        if (nit > 0) {
            const int pad = nit * 8 - cnt;
            const uint4 s0 = lds128(lsrc), s1 = lds128(lsrc + 16);
            const uint32_t eo = lds32(lsrc + lec);
            const uint32_t sv[8] = {s0.x, s0.y, s0.z, s0.w, s1.x, s1.y, s1.z, s1.w};
#pragma unroll
            for (int j = 0; j < 8; j++) cp16z(ring0 + (cpo ^ (j << 4)) + j * 512, madw(sv[j] & 0x3FFF, 512, tab_l), (j >= pad) ? 16 : 0);
            cp16z(ring0 + elo, madw(eo >> 14, 32, e_l), (rr >= pad) ? 16 : 0);
        }
        cp_commit();
    };
    auto issue1 = [&]() {
        if ((int)lds32(sb + SM_TCNT + w * 4) > 8) issue_full(lsrc + 32, RD);
        cp_commit();
    };
    uint32_t bar_v = 0;
    bool over = false;
    if (tid == 0) asm volatile("ld.relaxed.gpu.global.u32 %0, [%1];" : "=r"(bar_v) : "l"(p.bar) : "memory");
    if (!slow) {
        const uint2 tn = lds64(sb + SM_TNODE + w * 8);
        const uint4 dg = lds128(sb + SM_TDEG + w * 32);
        const uint32_t p1 = dg.x, p2 = p1 + dg.y, p3 = p2 + dg.z, p4 = p3 + dg.w, tot = p4 + lds32(sb + SM_TDEG + w * 32 + 16);
        const uint32_t pad = (0u - tot) & 7u;
        if (lane == 0) sts32(sb + SM_TCNT + w * 4, tot);
        over = tot + pad > TCAP;
        uint32_t wd[TCAP / 32], sl[TCAP / 32];
#pragma unroll
        for (int r = 0; r < TCAP / 32; r++) {
            const uint32_t q = lane + 32 * r - pad;
            sl[r] = (q >= p1) + (q >= p2) + (q >= p3) + (q >= p4);
            const uint32_t pre = (q >= p4) ? p4 : ((q >= p3) ? p3 : ((q >= p2) ? p2 : ((q >= p1) ? p1 : 0)));
            const uint32_t node = prmt(tn.x, tn.y, sl[r]) & 0xFF;
            wd[r] = lds32(sb + SM_NL + ((q < tot) ? (node * NCAP + q - pre) * 4 : 0));
        }
#pragma unroll
        for (int r = 0; r < TCAP / 32; r++) {
            const uint32_t q = lane + 32 * r - pad;
            sts32(lsrc + (lane + 32 * r) * 4, (q < tot) ? wd[r] : 0);
            sts8(lid + lane + 32 * r, (q < tot) ? sl[r] * 16 : 0x7F);
        }
    }
    if (tid == 0) {
        int it = 0;
        while ((int)(bar_v - bar_target) < 0 && ++it < SPIN_LIMIT)
            asm volatile("ld.relaxed.gpu.global.u32 %0, [%1];" : "=r"(bar_v) : "l"(p.bar) : "memory");
    }
    slow = __syncthreads_or(slow || over);
    if (!slow) {
        issue0();
        issue1();
    } else {
        if (tid < NPC) sts8(sb + SM_TNODE + (tid & 15) * 8 + (tid >> 4), tid);
        __syncthreads();
    }
    load_node_frags();

    const uint32_t ldo = rr * 512 + ((mi ^ rr) << 4);
    const uint32_t sel = (g | ((8 | g) << 4) | (g << 8) | ((8 | g) << 12)) |
                         (((2 * t) | ((8 | (2 * t)) << 4) | ((2 * t + 1) << 8) | ((8 | (2 * t + 1)) << 12)) << 16);
    const uint32_t gg = (g * 16) | ((g * 16) << 16);
    const uint32_t tt = (t * 32) | ((t * 32 + 16) << 16);

    auto compute = [&](uint32_t st, uint32_t idp) {
        uint32_t eb[2];
        ldsm2(eb, st + elo);
        const uint2 iw = lds64(idp);
        const uint32_t sx = seteq_bf16x2(prmt(iw.x, iw.y, sel), tt);
        const uint32_t sa = seteq_bf16x2(prmt(iw.x, iw.y, sel >> 16), gg);
#pragma unroll
        for (int jj = 0; jj < 4; jj++) {
            uint32_t xb[4], hv[4];
            const uint32_t la = st + (ldo ^ ((jj & 1) << 6)) + (jj >> 1) * 128;
            ldsm4(xb, la);
            ldsm4t(hv, la + 256);
#pragma unroll
            for (int u = 0; u < 2; u++) {
                const int j = 2 * jj + u;
                float d[4];
                mma16816_z(d, Cf[j][0], Cf[j][1], Cf[j][2], Cf[j][3], eb[0], eb[1]);
                mma1688(d, xAf[j][0], xAf[j][1], sx);
                mma16816(d, ident, 0u, 0u, ident, xb[2 * u], xb[2 * u + 1]);
                const uint32_t m0 = fma_bf16x2(pack_bf16(tanh_ap(d[0]), tanh_ap(d[1])), hv[2 * u], hv[2 * u]);
                const uint32_t m1 = fma_bf16x2(pack_bf16(tanh_ap(d[2]), tanh_ap(d[3])), hv[2 * u + 1], hv[2 * u + 1]);
                mma1688(agg[j], m0, m1, sa);
            }
        }
    };

    const int nseg = slow ? NSEG : 1;
#pragma unroll 1
    for (int seg = 0; seg < nseg; seg++) {
        if (slow) {
            __syncthreads();
            if (tid < 16) sts32(sb + SM_TCNT + tid * 4, 0);
            __syncthreads();
            const int e = seg * TCAP + tid;
            int loc = -1; uint32_t r = 0;
            if (tid < TCAP && e < EE) {
                const int dd = __ldg(p.dst + e) - b * NPC;
                if (dd >= 0 && dd < NPC) { loc = dd; r = atoms_add(sb + SM_TCNT + (loc & 15) * 4, 1); }
            }
            __syncthreads();
            if (loc >= 0) {
                const uint32_t tile = loc & 15, tot = lds32(sb + SM_TCNT + tile * 4);
                const uint32_t pos = tile * TCAP + ((0u - tot) & 7u) + r;
                sts32(sb + SM_LSE + pos * 4, (uint32_t)__ldg(p.src + e) | ((uint32_t)e << 14));
                sts8(sb + SM_LID + pos, (loc >> 4) << 4);
            }
            const int pad = (0 - (int)lds32(sb + SM_TCNT + w * 4)) & 7;
            if (lane < pad) { sts8(sb + SM_LID + w * TCAP + lane, 0x7F); sts32(sb + SM_LSE + (w * TCAP + lane) * 4, 0); }
            __syncthreads();
            issue0();
            issue1();
        }
        const int nit = __shfl_sync(0xffffffffu, ((int)lds32(sb + SM_TCNT + w * 4) + 7) >> 3, 0);
        uint32_t st = ring0, so = ring0 + RD, idp = lid;
        const uint32_t lend = lsrc + nit * 32;
        constexpr int AVG_NIT = (EE + NCTA * 128 - 1) / (NCTA * 128);
        constexpr int HEAVY = EE / NN * NPC * 207 / 200;
        const int ctot = __reduce_add_sync(0xffffffffu, (lane < 16) ? (int)lds32(sb + SM_TCNT + lane * 4) : 0);
        const bool eager = nit > AVG_NIT || ctot > HEAVY;
        uint32_t lc = lsrc + 32;
        uint32_t li = min(lsrc + 64, lend);
#pragma unroll 1
        for (; lc <= lend; lc += 32, idp += 8) {
            if (li > lc) cp_wait<1>(); else cp_wait<0>();
            __syncwarp();
            if (li == lc && li < lend) { issue_full(li, so - ring0); cp_commit(); li += 32; }
            compute(st, idp);
            if (eager && li == lc + 32 && li < lend) { __syncwarp(); issue_full(li, st - ring0); cp_commit(); li += 32; }
            const uint32_t tmp = st; st = so; so = tmp;
        }
        cp_wait<0>();
        __syncwarp();
    }

    {
        uint32_t o[8][2];
#pragma unroll
        for (int j = 0; j < 8; j++) {
            float v[4];
#pragma unroll
            for (int q = 0; q < 4; q++) { const float h = agg[j][q]; v[q] = fmaf(h, tanh_ap(h), h); }
            o[j][0] = pack_bf16(v[0], v[1]); o[j][1] = pack_bf16(v[2], v[3]);
        }
#pragma unroll
        for (int jp = 0; jp < 4; jp++) {
            const int c = 4 * jp + mi;
            stsm4t(ring0 + rr * 256 + ((c & 8) << 4) + (((c & 7) ^ rr) << 4), o[2 * jp][0], o[2 * jp][1], o[2 * jp + 1][0], o[2 * jp + 1][1]);
        }
        __syncwarp();
#pragma unroll
        for (int i = 0; i < 3; i++) {
            const int idx = lane + 32 * i, row = idx >> 4, c = idx & 15;
            const int nd = b * NPC + (int)lds8(sb + SM_TNODE + w * 8 + (row & 7));
            if (row < nslot && nd < NN) {
                const uint4 v = lds128(ring0 + row * 256 + ((c & 8) << 4) + (((c & 7) ^ row) << 4));
                *(uint4*)((char*)p.out + (size_t)nd * 256 + c * 16) = v;
            }
        }
    }
}

__device__ __align__(16) bf16 g_fb_xa[NN * 128];
__device__ __align__(16) float g_fb_h[NN * 128];

__global__ void fb_node_kernel(const bf16* x, const bf16* uw, const bf16* vw, const bf16* gw, bf16* table) {
    __shared__ float xs[128];
    const int n = blockIdx.x, f = threadIdx.x;
    xs[f] = __bfloat162float(x[n * 128 + f]);
    __syncthreads();
    float a = 0.f, bb = 0.f, v = 0.f, u = 0.f;
    for (int k = 0; k < 128; k++) {
        const float xv = xs[k];
        a += xv * __bfloat162float(gw[k * 128 + f]);
        bb += xv * __bfloat162float(gw[(128 + k) * 128 + f]);
        v += xv * __bfloat162float(vw[k * 128 + f]);
        u += xv * __bfloat162float(uw[k * 128 + f]);
    }
    table[n * 256 + f] = __float2bfloat16(0.5f * bb);
    table[n * 256 + 128 + f] = __float2bfloat16(0.25f * v);
    g_fb_xa[n * 128 + f] = __float2bfloat16(0.5f * a);
    g_fb_h[n * 128 + f] = 0.5f * u;
}
__global__ void fb_edge_kernel(const bf16* e_attr, const int* src, const int* dst, const bf16* gw, const bf16* table) {
    const int e = blockIdx.x, f = threadIdx.x, s = src[e], d = dst[e];
    float z = 0.f;
    for (int k = 0; k < 16; k++) z += __bfloat162float(e_attr[e * 16 + k]) * __bfloat162float(gw[(256 + k) * 128 + f]);
    z = 0.5f * z + __bfloat162float(g_fb_xa[d * 128 + f]) + __bfloat162float(table[s * 256 + f]);
    const float hv = __bfloat162float(table[s * 256 + 128 + f]);
    atomicAdd(&g_fb_h[d * 128 + f], fmaf(hv, tanhf(z), hv));
}
__global__ void fb_out_kernel(bf16* out) {
    const int i = blockIdx.x * 128 + threadIdx.x;
    const float h = g_fb_h[i];
    out[i] = __float2bfloat16(fmaf(h, tanhf(h), h));
}

typedef CUresult (*EncodeFn)(CUtensorMap*, CUtensorMapDataType, cuuint32_t, void*, const cuuint64_t*, const cuuint64_t*,
                             const cuuint32_t*, const cuuint32_t*, CUtensorMapInterleave, CUtensorMapSwizzle,
                             CUtensorMapL2promotion, CUtensorMapFloatOOBfill);

static void make_map(EncodeFn enc, CUtensorMap* tm, const void* base, int rows, int cols, int box_rows) {
    cuuint64_t dims[2] = {(cuuint64_t)cols, (cuuint64_t)rows};
    cuuint64_t strides[1] = {(cuuint64_t)cols * 2};
    cuuint32_t box[2] = {64, (cuuint32_t)box_rows};
    cuuint32_t es[2] = {1, 1};
    enc(tm, CU_TENSOR_MAP_DATA_TYPE_BFLOAT16, 2, (void*)base, dims, strides, box, es, CU_TENSOR_MAP_INTERLEAVE_NONE,
        CU_TENSOR_MAP_SWIZZLE_128B, CU_TENSOR_MAP_L2_PROMOTION_NONE, CU_TENSOR_MAP_FLOAT_OOB_FILL_NONE);
}

}

extern "C" void kernel_launch(void* const* d_in, const int* in_sizes, int n_in, void* d_out, int out_size) {
    using namespace egc;
    (void)in_sizes; (void)n_in; (void)out_size;
    static EncodeFn enc = nullptr;
    static void* table = nullptr;
    static void* xch = nullptr;
    static void* bar = nullptr;
    static bool persistent = false;
    if (!enc) {
        void* fn = nullptr;
        cudaDriverEntryPointQueryResult qr;
        cudaGetDriverEntryPoint("cuTensorMapEncodeTiled", &fn, cudaEnableDefault, &qr);
        enc = (EncodeFn)fn;
        cudaGetSymbolAddress(&table, g_table);
        cudaGetSymbolAddress(&xch, g_xch);
        cudaGetSymbolAddress(&bar, g_bar);
        cudaFuncSetAttribute(egc_kernel, cudaFuncAttributeMaxDynamicSharedMemorySize, SMEM_BYTES);
        int dev = 0, sms = 0, per_sm = 0;
        cudaGetDevice(&dev);
        cudaDeviceGetAttribute(&sms, cudaDevAttrMultiProcessorCount, dev);
        cudaOccupancyMaxActiveBlocksPerMultiprocessor(&per_sm, egc_kernel, NTHR, SMEM_BYTES);
        persistent = enc != nullptr && sms * per_sm >= NCTA;
    }
    if (!persistent) {
        const bf16* x = (const bf16*)d_in[0];
        fb_node_kernel<<<NN, 128, 0, cudaStreamPerThread>>>(x, (const bf16*)d_in[4], (const bf16*)d_in[5], (const bf16*)d_in[6], (bf16*)table);
        fb_edge_kernel<<<EE, 128, 0, cudaStreamPerThread>>>((const bf16*)d_in[1], (const int*)d_in[2], (const int*)d_in[3], (const bf16*)d_in[6], (const bf16*)table);
        fb_out_kernel<<<NN, 128, 0, cudaStreamPerThread>>>((bf16*)d_out);
        return;
    }
    CUtensorMap tm_x, tm_g, tm_u, tm_v, tm_t;
    make_map(enc, &tm_x, d_in[0], NN, 128, 80);
    make_map(enc, &tm_u, d_in[4], 128, 128, 128);
    make_map(enc, &tm_v, d_in[5], 128, 128, 128);
    make_map(enc, &tm_g, d_in[6], 272, 128, 128);
    make_map(enc, &tm_t, table, NN, 256, NPC);
    Params p;
    p.e_attr = (const bf16*)d_in[1];
    p.src = (const int*)d_in[2];
    p.dst = (const int*)d_in[3];
    p.gw = (const bf16*)d_in[6];
    p.out = (bf16*)d_out;
    p.bar = (unsigned*)bar;
    p.xch = (uint4*)xch;
    p.table = (const char*)table;
    egc_kernel<<<NCTA, NTHR, SMEM_BYTES, cudaStreamPerThread>>>(p, tm_x, tm_g, tm_u, tm_v, tm_t);
}
```
